```python
import torch

def _softmax(x, axis=-1):
    return torch.softmax(x, dim=axis)
def _gelu(x):
    return torch.nn.functional.gelu(x, approximate="tanh")
def _silu(x):
    return torch.nn.functional.silu(x)
def _sigmoid(x):
    return torch.sigmoid(x)
def _layernorm(x, axis=-1, eps=1e-5):
    m = x.mean(dim=axis, keepdim=True)
    v = x.var(dim=axis, keepdim=True, unbiased=False)
    return (x - m) / torch.sqrt(v + eps)
def _scatter_add(tgt, idx, src, axis=0):
    return tgt.clone().index_add_(axis, idx, src)
def _segment_sum(src, seg, n):
    out = torch.zeros((n,) + src.shape[1:], dtype=src.dtype)
    return out.index_add_(0, seg, src)
def _pad(x, pw):
    flat = tuple(v for pair in reversed(pw) for v in pair)
    return torch.nn.functional.pad(x, flat)

kernel_name = 'gather_scatter__hybrid_graph_tf_graphgps__graph'

def setup_inputs():

    _w = (lambda a: (lambda t: t.to(torch.bfloat16) if t.is_floating_point() else t)(torch.as_tensor(a)))
    N, deg, D = 10000, 16, 128
    E = N * deg
    src = (lambda lo, hi, *s: torch.randint(lo, hi, s))(0, N, E).to(torch.int64)
    dst = (lambda lo, hi, *s: torch.randint(lo, hi, s))(0, N, E).to(torch.int64)
    deg_cnt = torch.bincount(dst, minlength=N).to(float) + 1.0
    sc = 1.0 / float(D) ** 0.5
    return {
        "x": _w((lambda *s: torch.randn(*s, dtype=torch.bfloat16) * 0.05)(N, D)),
        "src": _w(src),
        "dst": _w(dst),
        "deg_inv": _w((1.0 / deg_cnt).to(float)),
        "w_msg": _w((lambda *s: torch.randn(*s, dtype=torch.bfloat16) * 0.2)(D, D) * sc),
        "wq": _w((lambda *s: torch.randn(*s, dtype=torch.bfloat16) * 1.6)(D, D) * sc),
        "wk": _w((lambda *s: torch.randn(*s, dtype=torch.bfloat16) * 1.6)(D, D) * sc),
        "wv": _w((lambda *s: torch.randn(*s, dtype=torch.bfloat16) * 0.2)(D, D) * sc),
        "w_out": _w((lambda *s: torch.randn(*s, dtype=torch.bfloat16) * 0.2)(D, D) * sc),
    }

def reference(x, src, dst, deg_inv, w_msg, wq, wk, wv, w_out):
    N, D = x.shape[0], x.shape[1]
    h = _layernorm(x, axis=-1)
    m_e = torch.einsum('nd,de->ne', h, w_msg)
    h_local = _segment_sum(m_e[src], dst, N) * deg_inv[:, None]
    q = torch.einsum('nd,de->ne', h, wq)
    k = torch.einsum('nd,de->ne', h, wk)
    v = torch.einsum('nd,de->ne', h, wv)
    logits = torch.einsum('id,jd->ij', q, k) / (float(D) ** 0.5)
    attn = _softmax(logits, axis=-1)
    h_global = torch.einsum('ij,jd->id', attn, v)
    y = torch.einsum('nd,de->ne', h_local + h_global, w_out)
    return x + y
```

```cpp
#include <cuda_runtime.h>
#include <cuda_bf16.h>
#include <cuda_fp16.h>
#include <stdint.h>

namespace {

constexpr int NN = 10000;
constexpr int EE = 160000;
constexpr int NPAD = 10112;
constexpr int T = 144;
constexpr int NST = 4;
constexpr uint32_t TILE_B = T * 256;
constexpr int CAP = 32;
constexpr int NCTA = 132;
constexpr float COFF = 10.f;
constexpr float RS1 = 0.09695833f;
constexpr float RSN = 0.08838835f;
constexpr float QSCALE = 0.12751744f;
constexpr int SPIN = 1 << 20;

constexpr uint32_t SM_KV = 0;
constexpr uint32_t SM_G = NST * TILE_B;
constexpr uint32_t SM_M = SM_G + 32768;
constexpr uint32_t SM_LAM = SM_M + 32768;
constexpr uint32_t SM_M2 = SM_LAM + 2048;
constexpr uint32_t SM_BAR = SM_M2 + 2048;
constexpr uint32_t SM_TOTAL = SM_BAR + 256 + 1024;
enum { B_FULL = 0, B_EMPTY = NST, B_WQ = 2 * NST, B_WK, B_WZ, B_WFREE, B_G, B_M, B_Q2, B_TAG };

constexpr int PART_B = 16384 + 1024;

__device__ __align__(1024) uint8_t g_h[NPAD * 256];
__device__ float2 g_stats[NPAD];
__device__ int g_cnt[NPAD];
__device__ __align__(128) uint16_t g_ell[NPAD * CAP];
__device__ int g_ovf_head[NPAD];
__device__ int g_ovf_next[EE];
__device__ __align__(1024) uint8_t g_part[26 * 2 * 2 * PART_B];
__device__ __align__(1024) uint8_t g_wc[2 * 32768];
__device__ unsigned g_hflag[160];
__device__ unsigned g_pflag[26 * 4];
__device__ unsigned g_wflag[4];
__device__ unsigned long long g_ticket;
__device__ unsigned long long g_ellctr;
#define PROBE(k)
#define PROBE1(k)

__device__ __forceinline__ void mma_qk(float (&d)[72], uint32_t a0, uint32_t a1, uint32_t a2, uint32_t a3, uint64_t db, int scale_d) {
  asm volatile("{\n.reg .pred p;\nsetp.ne.b32 p, %77, 0;\n"
    "wgmma.mma_async.sync.aligned.m64n144k16.f32.f16.f16 {"
    "%0, %1, %2, %3, %4, %5, %6, %7, %8, %9, %10, %11, %12, %13, %14, %15, "
    "%16, %17, %18, %19, %20, %21, %22, %23, %24, %25, %26, %27, %28, %29, %30, %31, "
    "%32, %33, %34, %35, %36, %37, %38, %39, %40, %41, %42, %43, %44, %45, %46, %47, "
    "%48, %49, %50, %51, %52, %53, %54, %55, %56, %57, %58, %59, %60, %61, %62, %63, "
    "%64, %65, %66, %67, %68, %69, %70, %71}, "
    "{%72, %73, %74, %75}, %76, p, 1, 1, 0;\n}\n"
    : "+f"(d[0]), "+f"(d[1]), "+f"(d[2]), "+f"(d[3]), "+f"(d[4]), "+f"(d[5]), "+f"(d[6]), "+f"(d[7]),
      "+f"(d[8]), "+f"(d[9]), "+f"(d[10]), "+f"(d[11]), "+f"(d[12]), "+f"(d[13]), "+f"(d[14]), "+f"(d[15]),
      "+f"(d[16]), "+f"(d[17]), "+f"(d[18]), "+f"(d[19]), "+f"(d[20]), "+f"(d[21]), "+f"(d[22]), "+f"(d[23]),
      "+f"(d[24]), "+f"(d[25]), "+f"(d[26]), "+f"(d[27]), "+f"(d[28]), "+f"(d[29]), "+f"(d[30]), "+f"(d[31]),
      "+f"(d[32]), "+f"(d[33]), "+f"(d[34]), "+f"(d[35]), "+f"(d[36]), "+f"(d[37]), "+f"(d[38]), "+f"(d[39]),
      "+f"(d[40]), "+f"(d[41]), "+f"(d[42]), "+f"(d[43]), "+f"(d[44]), "+f"(d[45]), "+f"(d[46]), "+f"(d[47]),
      "+f"(d[48]), "+f"(d[49]), "+f"(d[50]), "+f"(d[51]), "+f"(d[52]), "+f"(d[53]), "+f"(d[54]), "+f"(d[55]),
      "+f"(d[56]), "+f"(d[57]), "+f"(d[58]), "+f"(d[59]), "+f"(d[60]), "+f"(d[61]), "+f"(d[62]), "+f"(d[63]),
      "+f"(d[64]), "+f"(d[65]), "+f"(d[66]), "+f"(d[67]), "+f"(d[68]), "+f"(d[69]), "+f"(d[70]), "+f"(d[71])
    : "r"(a0), "r"(a1), "r"(a2), "r"(a3), "l"(db), "r"(scale_d));
}
__device__ __forceinline__ void mma_pv(float (&d)[64], uint32_t a0, uint32_t a1, uint32_t a2, uint32_t a3, uint64_t db, int scale_d) {
  asm volatile("{\n.reg .pred p;\nsetp.ne.b32 p, %69, 0;\n"
    "wgmma.mma_async.sync.aligned.m64n128k16.f32.f16.f16 {"
    "%0, %1, %2, %3, %4, %5, %6, %7, %8, %9, %10, %11, %12, %13, %14, %15, "
    "%16, %17, %18, %19, %20, %21, %22, %23, %24, %25, %26, %27, %28, %29, %30, %31, "
    "%32, %33, %34, %35, %36, %37, %38, %39, %40, %41, %42, %43, %44, %45, %46, %47, "
    "%48, %49, %50, %51, %52, %53, %54, %55, %56, %57, %58, %59, %60, %61, %62, %63}, "
    "{%64, %65, %66, %67}, %68, p, 1, 1, 1;\n}\n"
    : "+f"(d[0]), "+f"(d[1]), "+f"(d[2]), "+f"(d[3]), "+f"(d[4]), "+f"(d[5]), "+f"(d[6]), "+f"(d[7]),
      "+f"(d[8]), "+f"(d[9]), "+f"(d[10]), "+f"(d[11]), "+f"(d[12]), "+f"(d[13]), "+f"(d[14]), "+f"(d[15]),
      "+f"(d[16]), "+f"(d[17]), "+f"(d[18]), "+f"(d[19]), "+f"(d[20]), "+f"(d[21]), "+f"(d[22]), "+f"(d[23]),
      "+f"(d[24]), "+f"(d[25]), "+f"(d[26]), "+f"(d[27]), "+f"(d[28]), "+f"(d[29]), "+f"(d[30]), "+f"(d[31]),
      "+f"(d[32]), "+f"(d[33]), "+f"(d[34]), "+f"(d[35]), "+f"(d[36]), "+f"(d[37]), "+f"(d[38]), "+f"(d[39]),
      "+f"(d[40]), "+f"(d[41]), "+f"(d[42]), "+f"(d[43]), "+f"(d[44]), "+f"(d[45]), "+f"(d[46]), "+f"(d[47]),
      "+f"(d[48]), "+f"(d[49]), "+f"(d[50]), "+f"(d[51]), "+f"(d[52]), "+f"(d[53]), "+f"(d[54]), "+f"(d[55]),
      "+f"(d[56]), "+f"(d[57]), "+f"(d[58]), "+f"(d[59]), "+f"(d[60]), "+f"(d[61]), "+f"(d[62]), "+f"(d[63])
    : "r"(a0), "r"(a1), "r"(a2), "r"(a3), "l"(db), "r"(scale_d));
}
__device__ __forceinline__ void mma_rs_t(float (&d)[64], uint32_t a0, uint32_t a1, uint32_t a2, uint32_t a3, uint64_t db, int scale_d) {
  asm volatile("{\n.reg .pred p;\nsetp.ne.b32 p, %69, 0;\n"
    "wgmma.mma_async.sync.aligned.m64n128k16.f32.bf16.bf16 {"
    "%0, %1, %2, %3, %4, %5, %6, %7, %8, %9, %10, %11, %12, %13, %14, %15, "
    "%16, %17, %18, %19, %20, %21, %22, %23, %24, %25, %26, %27, %28, %29, %30, %31, "
    "%32, %33, %34, %35, %36, %37, %38, %39, %40, %41, %42, %43, %44, %45, %46, %47, "
    "%48, %49, %50, %51, %52, %53, %54, %55, %56, %57, %58, %59, %60, %61, %62, %63}, "
    "{%64, %65, %66, %67}, %68, p, 1, 1, 1;\n}\n"
    : "+f"(d[0]), "+f"(d[1]), "+f"(d[2]), "+f"(d[3]), "+f"(d[4]), "+f"(d[5]), "+f"(d[6]), "+f"(d[7]),
      "+f"(d[8]), "+f"(d[9]), "+f"(d[10]), "+f"(d[11]), "+f"(d[12]), "+f"(d[13]), "+f"(d[14]), "+f"(d[15]),
      "+f"(d[16]), "+f"(d[17]), "+f"(d[18]), "+f"(d[19]), "+f"(d[20]), "+f"(d[21]), "+f"(d[22]), "+f"(d[23]),
      "+f"(d[24]), "+f"(d[25]), "+f"(d[26]), "+f"(d[27]), "+f"(d[28]), "+f"(d[29]), "+f"(d[30]), "+f"(d[31]),
      "+f"(d[32]), "+f"(d[33]), "+f"(d[34]), "+f"(d[35]), "+f"(d[36]), "+f"(d[37]), "+f"(d[38]), "+f"(d[39]),
      "+f"(d[40]), "+f"(d[41]), "+f"(d[42]), "+f"(d[43]), "+f"(d[44]), "+f"(d[45]), "+f"(d[46]), "+f"(d[47]),
      "+f"(d[48]), "+f"(d[49]), "+f"(d[50]), "+f"(d[51]), "+f"(d[52]), "+f"(d[53]), "+f"(d[54]), "+f"(d[55]),
      "+f"(d[56]), "+f"(d[57]), "+f"(d[58]), "+f"(d[59]), "+f"(d[60]), "+f"(d[61]), "+f"(d[62]), "+f"(d[63])
    : "r"(a0), "r"(a1), "r"(a2), "r"(a3), "l"(db), "r"(scale_d));
}
__device__ __forceinline__ void mma_rs(float (&d)[64], uint32_t a0, uint32_t a1, uint32_t a2, uint32_t a3, uint64_t db, int scale_d) {
  asm volatile("{\n.reg .pred p;\nsetp.ne.b32 p, %69, 0;\n"
    "wgmma.mma_async.sync.aligned.m64n128k16.f32.bf16.bf16 {"
    "%0, %1, %2, %3, %4, %5, %6, %7, %8, %9, %10, %11, %12, %13, %14, %15, "
    "%16, %17, %18, %19, %20, %21, %22, %23, %24, %25, %26, %27, %28, %29, %30, %31, "
    "%32, %33, %34, %35, %36, %37, %38, %39, %40, %41, %42, %43, %44, %45, %46, %47, "
    "%48, %49, %50, %51, %52, %53, %54, %55, %56, %57, %58, %59, %60, %61, %62, %63}, "
    "{%64, %65, %66, %67}, %68, p, 1, 1, 0;\n}\n"
    : "+f"(d[0]), "+f"(d[1]), "+f"(d[2]), "+f"(d[3]), "+f"(d[4]), "+f"(d[5]), "+f"(d[6]), "+f"(d[7]),
      "+f"(d[8]), "+f"(d[9]), "+f"(d[10]), "+f"(d[11]), "+f"(d[12]), "+f"(d[13]), "+f"(d[14]), "+f"(d[15]),
      "+f"(d[16]), "+f"(d[17]), "+f"(d[18]), "+f"(d[19]), "+f"(d[20]), "+f"(d[21]), "+f"(d[22]), "+f"(d[23]),
      "+f"(d[24]), "+f"(d[25]), "+f"(d[26]), "+f"(d[27]), "+f"(d[28]), "+f"(d[29]), "+f"(d[30]), "+f"(d[31]),
      "+f"(d[32]), "+f"(d[33]), "+f"(d[34]), "+f"(d[35]), "+f"(d[36]), "+f"(d[37]), "+f"(d[38]), "+f"(d[39]),
      "+f"(d[40]), "+f"(d[41]), "+f"(d[42]), "+f"(d[43]), "+f"(d[44]), "+f"(d[45]), "+f"(d[46]), "+f"(d[47]),
      "+f"(d[48]), "+f"(d[49]), "+f"(d[50]), "+f"(d[51]), "+f"(d[52]), "+f"(d[53]), "+f"(d[54]), "+f"(d[55]),
      "+f"(d[56]), "+f"(d[57]), "+f"(d[58]), "+f"(d[59]), "+f"(d[60]), "+f"(d[61]), "+f"(d[62]), "+f"(d[63])
    : "r"(a0), "r"(a1), "r"(a2), "r"(a3), "l"(db), "r"(scale_d));
}
__device__ __forceinline__ void mma_ss(float (&d)[64], uint64_t da, uint64_t db, int scale_d) {
  asm volatile("{\n.reg .pred p;\nsetp.ne.b32 p, %66, 0;\n"
    "wgmma.mma_async.sync.aligned.m64n128k16.f32.bf16.bf16 {"
    "%0, %1, %2, %3, %4, %5, %6, %7, %8, %9, %10, %11, %12, %13, %14, %15, "
    "%16, %17, %18, %19, %20, %21, %22, %23, %24, %25, %26, %27, %28, %29, %30, %31, "
    "%32, %33, %34, %35, %36, %37, %38, %39, %40, %41, %42, %43, %44, %45, %46, %47, "
    "%48, %49, %50, %51, %52, %53, %54, %55, %56, %57, %58, %59, %60, %61, %62, %63}, "
    "%64, %65, p, 1, 1, 0, 0;\n}\n"
    : "+f"(d[0]), "+f"(d[1]), "+f"(d[2]), "+f"(d[3]), "+f"(d[4]), "+f"(d[5]), "+f"(d[6]), "+f"(d[7]),
      "+f"(d[8]), "+f"(d[9]), "+f"(d[10]), "+f"(d[11]), "+f"(d[12]), "+f"(d[13]), "+f"(d[14]), "+f"(d[15]),
      "+f"(d[16]), "+f"(d[17]), "+f"(d[18]), "+f"(d[19]), "+f"(d[20]), "+f"(d[21]), "+f"(d[22]), "+f"(d[23]),
      "+f"(d[24]), "+f"(d[25]), "+f"(d[26]), "+f"(d[27]), "+f"(d[28]), "+f"(d[29]), "+f"(d[30]), "+f"(d[31]),
      "+f"(d[32]), "+f"(d[33]), "+f"(d[34]), "+f"(d[35]), "+f"(d[36]), "+f"(d[37]), "+f"(d[38]), "+f"(d[39]),
      "+f"(d[40]), "+f"(d[41]), "+f"(d[42]), "+f"(d[43]), "+f"(d[44]), "+f"(d[45]), "+f"(d[46]), "+f"(d[47]),
      "+f"(d[48]), "+f"(d[49]), "+f"(d[50]), "+f"(d[51]), "+f"(d[52]), "+f"(d[53]), "+f"(d[54]), "+f"(d[55]),
      "+f"(d[56]), "+f"(d[57]), "+f"(d[58]), "+f"(d[59]), "+f"(d[60]), "+f"(d[61]), "+f"(d[62]), "+f"(d[63])
    : "l"(da), "l"(db), "r"(scale_d));
}
__device__ __forceinline__ void mma_ss_ta(float (&d)[64], uint64_t da, uint64_t db, int scale_d) {
  asm volatile("{\n.reg .pred p;\nsetp.ne.b32 p, %66, 0;\n"
    "wgmma.mma_async.sync.aligned.m64n128k16.f32.bf16.bf16 {"
    "%0, %1, %2, %3, %4, %5, %6, %7, %8, %9, %10, %11, %12, %13, %14, %15, "
    "%16, %17, %18, %19, %20, %21, %22, %23, %24, %25, %26, %27, %28, %29, %30, %31, "
    "%32, %33, %34, %35, %36, %37, %38, %39, %40, %41, %42, %43, %44, %45, %46, %47, "
    "%48, %49, %50, %51, %52, %53, %54, %55, %56, %57, %58, %59, %60, %61, %62, %63}, "
    "%64, %65, p, 1, 1, 1, 0;\n}\n"
    : "+f"(d[0]), "+f"(d[1]), "+f"(d[2]), "+f"(d[3]), "+f"(d[4]), "+f"(d[5]), "+f"(d[6]), "+f"(d[7]),
      "+f"(d[8]), "+f"(d[9]), "+f"(d[10]), "+f"(d[11]), "+f"(d[12]), "+f"(d[13]), "+f"(d[14]), "+f"(d[15]),
      "+f"(d[16]), "+f"(d[17]), "+f"(d[18]), "+f"(d[19]), "+f"(d[20]), "+f"(d[21]), "+f"(d[22]), "+f"(d[23]),
      "+f"(d[24]), "+f"(d[25]), "+f"(d[26]), "+f"(d[27]), "+f"(d[28]), "+f"(d[29]), "+f"(d[30]), "+f"(d[31]),
      "+f"(d[32]), "+f"(d[33]), "+f"(d[34]), "+f"(d[35]), "+f"(d[36]), "+f"(d[37]), "+f"(d[38]), "+f"(d[39]),
      "+f"(d[40]), "+f"(d[41]), "+f"(d[42]), "+f"(d[43]), "+f"(d[44]), "+f"(d[45]), "+f"(d[46]), "+f"(d[47]),
      "+f"(d[48]), "+f"(d[49]), "+f"(d[50]), "+f"(d[51]), "+f"(d[52]), "+f"(d[53]), "+f"(d[54]), "+f"(d[55]),
      "+f"(d[56]), "+f"(d[57]), "+f"(d[58]), "+f"(d[59]), "+f"(d[60]), "+f"(d[61]), "+f"(d[62]), "+f"(d[63])
    : "l"(da), "l"(db), "r"(scale_d));
}

__device__ __forceinline__ void mbar_init(uint32_t bar, int cnt) { asm volatile("mbarrier.init.shared::cta.b64 [%0], %1;" :: "r"(bar), "r"(cnt) : "memory"); }
__device__ __forceinline__ void mbar_arrive(uint32_t bar) { asm volatile("mbarrier.arrive.shared::cta.b64 _, [%0];" :: "r"(bar) : "memory"); }
__device__ __forceinline__ void mbar_arrive_remote(uint32_t bar) { asm volatile("mbarrier.arrive.release.cluster.shared::cluster.b64 _, [%0];" :: "r"(bar) : "memory"); }
__device__ __forceinline__ void mbar_expect_tx(uint32_t bar, uint32_t bytes) { asm volatile("mbarrier.arrive.expect_tx.shared::cta.b64 _, [%0], %1;" :: "r"(bar), "r"(bytes) : "memory"); }
__device__ __forceinline__ void mbar_wait(uint32_t bar, uint32_t parity) {
  uint32_t ok; int it = 0;
  do {
    asm volatile("{\n.reg .pred p;\nmbarrier.try_wait.parity.shared::cta.b64 p, [%1], %2;\nselp.u32 %0, 1, 0, p;\n}\n" : "=r"(ok) : "r"(bar), "r"(parity) : "memory");
  } while (!ok && ++it < SPIN);
}
__device__ __forceinline__ void mbar_wait_cluster(uint32_t bar, uint32_t parity) {
  uint32_t ok; int it = 0;
  do {
    asm volatile("{\n.reg .pred p;\nmbarrier.try_wait.parity.acquire.cluster.shared::cta.b64 p, [%1], %2;\nselp.u32 %0, 1, 0, p;\n}\n" : "=r"(ok) : "r"(bar), "r"(parity) : "memory");
  } while (!ok && ++it < SPIN);
}
__device__ __forceinline__ void bulk_g2s(uint32_t dst, const void* src, uint32_t bytes, uint32_t bar) {
  asm volatile("cp.async.bulk.shared::cluster.global.mbarrier::complete_tx::bytes [%0], [%1], %2, [%3];" :: "r"(dst), "l"(src), "r"(bytes), "r"(bar) : "memory");
}
__device__ __forceinline__ void cp16(uint32_t dst, const void* src) { asm volatile("cp.async.cg.shared.global [%0], [%1], 16;" :: "r"(dst), "l"(src) : "memory"); }
__device__ __forceinline__ void cp_commit() { asm volatile("cp.async.commit_group;" ::: "memory"); }
template <int K> __device__ __forceinline__ void cp_wait() { asm volatile("cp.async.wait_group %0;" :: "n"(K) : "memory"); }
__device__ __forceinline__ void fence_async() { asm volatile("fence.proxy.async;" ::: "memory"); }
__device__ __forceinline__ void wg_fence() { asm volatile("wgmma.fence.sync.aligned;" ::: "memory"); }
__device__ __forceinline__ void wg_commit() { asm volatile("wgmma.commit_group.sync.aligned;" ::: "memory"); }
template <int K> __device__ __forceinline__ void wg_wait() { asm volatile("wgmma.wait_group.sync.aligned %0;" :: "n"(K) : "memory"); }
__device__ __forceinline__ void bar_sync(int id, int n) { asm volatile("bar.sync %0, %1;" :: "r"(id), "r"(n) : "memory"); }
__device__ __forceinline__ void bar_arrive(int id, int n) { asm volatile("bar.arrive %0, %1;" :: "r"(id), "r"(n) : "memory"); }
__device__ __forceinline__ float ex2(float x) { float y; asm("ex2.approx.ftz.f32 %0, %1;" : "=f"(y) : "f"(x)); return y; }
__device__ __forceinline__ float lg2(float x) { float y; asm("lg2.approx.f32 %0, %1;" : "=f"(y) : "f"(x)); return y; }
__device__ __forceinline__ uint32_t pack_bf16(float lo, float hi) { uint32_t r; asm("cvt.rn.bf16x2.f32 %0, %1, %2;" : "=r"(r) : "f"(hi), "f"(lo)); return r; }
__device__ __forceinline__ uint32_t pack_f16(float lo, float hi) { uint32_t r; asm("cvt.rn.f16x2.f32 %0, %1, %2;" : "=r"(r) : "f"(hi), "f"(lo)); return r; }
__device__ __forceinline__ uint32_t pack_f16_sat(float lo, float hi) { uint32_t r; asm("cvt.rn.satfinite.f16x2.f32 %0, %1, %2;" : "=r"(r) : "f"(hi), "f"(lo)); return r; }
__device__ __forceinline__ float bf_lo(uint32_t u) { return __uint_as_float(u << 16); }
__device__ __forceinline__ float bf_hi(uint32_t u) { return __uint_as_float(u & 0xffff0000u); }
__device__ __forceinline__ float h_lo(uint32_t u) { return __half2float(__ushort_as_half((unsigned short)(u & 0xffffu))); }
__device__ __forceinline__ float h_hi(uint32_t u) { return __half2float(__ushort_as_half((unsigned short)(u >> 16))); }
__device__ __forceinline__ float quad_sum(float v) { v += __shfl_xor_sync(~0u, v, 1); return v + __shfl_xor_sync(~0u, v, 2); }
__device__ __forceinline__ float quad_max(float v) { v = fmaxf(v, __shfl_xor_sync(~0u, v, 1)); return fmaxf(v, __shfl_xor_sync(~0u, v, 2)); }
template <int K> __device__ __forceinline__ void pin(float (&d)[K]) {
#pragma unroll
  for (int i = 0; i < K; i++) asm volatile("" : "+f"(d[i]) :: "memory");
}
template <int K> __device__ __forceinline__ void pin(uint32_t (&d)[K]) {
#pragma unroll
  for (int i = 0; i < K; i++) asm volatile("" : "+r"(d[i]) :: "memory");
}
__device__ __forceinline__ uint64_t desc_k(uint32_t a) { return (uint64_t)((a & 0x3FFFF) >> 4) | (1ull << 16) | (128ull << 32) | (1ull << 62); }
__device__ __forceinline__ uint64_t desc_mn(uint32_t a) { return (uint64_t)((a & 0x3FFFF) >> 4) | (64ull << 16) | (128ull << 32) | (1ull << 62); }
__device__ __forceinline__ constexpr uint32_t koff(int ks) { return ((ks >> 2) * 1024 + (ks & 3) * 32) >> 4; }
__device__ __forceinline__ uint32_t tile_off(int row, int chunk) { return (row >> 3) * 2048 + (chunk >> 3) * 1024 + (row & 7) * 128 + (((chunk & 7) ^ (row & 7)) << 4); }
__device__ __forceinline__ unsigned ld_acq(const unsigned* p) { unsigned v; asm volatile("ld.acquire.gpu.global.u32 %0, [%1];" : "=r"(v) : "l"(p) : "memory"); return v; }
__device__ __forceinline__ void st_rel(unsigned* p, unsigned v) { asm volatile("st.release.gpu.global.u32 [%0], %1;" :: "l"(p), "r"(v) : "memory"); }
__device__ __forceinline__ void wait_flag(const unsigned* p, unsigned tag) { int it = 0; while (ld_acq(p) != tag && ++it < SPIN) {} }
__device__ __forceinline__ uint32_t mapa(uint32_t a, uint32_t rank) { uint32_t r; asm("mapa.shared::cluster.u32 %0, %1, %2;" : "=r"(r) : "r"(a), "r"(rank)); return r; }
__device__ __forceinline__ void st_cl4(uint32_t a, uint32_t x, uint32_t y, uint32_t z, uint32_t w) { asm volatile("st.shared::cluster.v4.b32 [%0], {%1, %2, %3, %4};" :: "r"(a), "r"(x), "r"(y), "r"(z), "r"(w) : "memory"); }
__device__ __forceinline__ void st_cl2(uint32_t a, float x, float y) { asm volatile("st.shared::cluster.v2.f32 [%0], {%1, %2};" :: "r"(a), "f"(x), "f"(y) : "memory"); }
__device__ __forceinline__ uint4 lds4(uint32_t a) { uint4 v; asm volatile("ld.shared.v4.b32 {%0, %1, %2, %3}, [%4];" : "=r"(v.x), "=r"(v.y), "=r"(v.z), "=r"(v.w) : "r"(a) : "memory"); return v; }
__device__ __forceinline__ float2 lds2(uint32_t a) { float2 v; asm volatile("ld.shared.v2.f32 {%0, %1}, [%2];" : "=f"(v.x), "=f"(v.y) : "r"(a) : "memory"); return v; }

template <bool PERM> __device__ __forceinline__ void stage_w(uint32_t dst, const __nv_bfloat16* w, int t) {
#pragma unroll 4
  for (int i = 0; i < 16; i++) {
    int idx = i * 128 + t, r = idx >> 4, c = idx & 15;
    int lr = PERM ? (((r >> 5) * 2 + ((r >> 2) & 1)) * 16 + ((r >> 1) & 1) * 8 + ((r >> 3) & 3) * 2 + (r & 1)) : r;
    cp16(dst + tile_off(lr, c), w + idx * 8);
  }
}

__global__ void __launch_bounds__(384, 1) __cluster_dims__(2, 1, 1)
graphgps_kernel(const __nv_bfloat16* __restrict__ x, const int* __restrict__ esrc, const int* __restrict__ edst,
                const __nv_bfloat16* __restrict__ deg_inv, const __nv_bfloat16* __restrict__ wmsg,
                const __nv_bfloat16* __restrict__ wq, const __nv_bfloat16* __restrict__ wk,
                const __nv_bfloat16* __restrict__ wv, const __nv_bfloat16* __restrict__ wout,
                __nv_bfloat16* __restrict__ out) {
  extern __shared__ uint8_t smem_raw[];
  const uint32_t sb = ((uint32_t)__cvta_generic_to_shared(smem_raw) + 1023) & ~1023u;
  const uint32_t bars = sb + SM_BAR;
  const int tid = threadIdx.x, lane = tid & 31;
  const int wg = __shfl_sync(~0u, tid >> 7, 0);
  const int cl = blockIdx.x >> 1, rank = blockIdx.x & 1;
  const bool isY = cl >= 52 && cl < 65, isZ = cl == 65, isX1 = cl < 52 && rank == 1, isX0 = cl < 52 && rank == 0;
  const int grp = isY ? (cl - 52) * 2 + rank : cl >> 1;
  const int qfin = isZ ? 78 : isY ? 3 * grp + 1 : 3 * grp + (cl & 1) * 2;
  const int ntiles = isZ ? 35 : 42;
  const int jsw = isX1 ? 14 : 0;
  const bool writes_h = !isX1 && !(isZ && rank == 1);
  PROBE(wg == 2 ? 0 : 31);

  if (tid == 256) {
    for (int i = 0; i < NST; i++) { mbar_init(bars + 8 * (B_FULL + i), 1); mbar_init(bars + 8 * (B_EMPTY + i), 2); }
    mbar_init(bars + 8 * B_WQ, 128); mbar_init(bars + 8 * B_WK, 128); mbar_init(bars + 8 * B_WZ, 128);
    mbar_init(bars + 8 * B_WFREE, 2); mbar_init(bars + 8 * B_G, 96); mbar_init(bars + 8 * B_M, isY ? 96 : 128);
    mbar_init(bars + 8 * B_Q2, 256);
    asm volatile("fence.mbarrier_init.release.cluster;" ::: "memory");
  }

  if (wg == 2) {
    asm volatile("setmaxnreg.dec.sync.aligned.u32 40;");
    const int t = tid - 256, pw = __shfl_sync(~0u, t >> 5, 0);
    stage_w<true>(sb + SM_KV + 2 * TILE_B, wq, t); cp_commit();
    stage_w<false>(sb + SM_KV + 3 * TILE_B, wk, t); cp_commit();
    if (isZ) { stage_w<false>(sb + SM_G, wout, t); stage_w<false>(sb + SM_M, rank ? wv : wmsg, t); }
    cp_commit();
    bar_sync(0, 384);
    asm volatile("barrier.cluster.arrive.release.aligned;" ::: "memory");
    if (t == 0) {
      unsigned long long tk = atomicAdd(&g_ticket, 1ull);
      asm volatile("st.shared.u64 [%0], %1;" :: "r"(bars + 8 * B_TAG), "l"(tk / NCTA + 1) : "memory");
    }
    cp_wait<2>(); fence_async(); mbar_arrive(bars + 8 * B_WQ);
    cp_wait<1>(); fence_async(); mbar_arrive(bars + 8 * B_WK);
    bar_sync(5, 128);
    unsigned long long epoch; asm volatile("ld.shared.u64 %0, [%1];" : "=l"(epoch) : "r"(bars + 8 * B_TAG) : "memory");
    const unsigned tag = (unsigned)epoch;
    if (writes_h && (pw == 1 || pw == 2)) {
      bar_sync(2 + pw, 160);
      const int blk = isY ? pw - 1 : pw & 1;
      if (lane == 0) { __threadfence(); st_rel(&g_hflag[qfin * 2 + blk], tag); }
      PROBE1(20 + pw);
    }
    cp_wait<0>(); fence_async(); mbar_arrive(bars + 8 * B_WZ);
    asm volatile("barrier.cluster.wait.acquire.aligned;" ::: "memory");
    if (pw == 0) {
      const int kvA = isX1 ? (cl & 1) * 56 : 0;
      const int kvB = isZ ? rank * 35 : isY ? 14 : isX1 ? 42 : 0;
      int st = 0, ph = 1;
      for (int j = 0; j < ntiles + 2; j++) {
        const int tile = j < jsw ? kvA + j : kvB + (j - jsw);
        if (j < ntiles) { if (lane < 4) wait_flag(&g_hflag[min((tile * T >> 6) + lane, (tile * T + T - 1) >> 6)], tag); }
        else if (lane < 2) wait_flag(&g_wflag[(j - ntiles) * 2 + lane], tag);
        __syncwarp();
        if (lane == 0) {
          fence_async();
          if (j == 2) mbar_wait(bars + 8 * B_WFREE, 0);
          mbar_wait(bars + 8 * (B_EMPTY + st), ph);
          const uint32_t bytes = j < ntiles ? TILE_B : 32768u;
          mbar_expect_tx(bars + 8 * (B_FULL + st), bytes);
          bulk_g2s(sb + SM_KV + st * TILE_B, j < ntiles ? g_h + (size_t)tile * TILE_B : g_wc + (j - ntiles) * 32768, bytes, bars + 8 * (B_FULL + st));
        }
        if (j == 0) PROBE1(1);
        __syncwarp();
        if (++st == NST) { st = 0; ph ^= 1; }
      }
    } else {
      const int gt = t - 32, gw = pw - 1;
      if (isZ && gw < 2) {
        bar_sync(6 + gw, 160);
        if (lane == 0) { __threadfence(); st_rel(&g_wflag[rank * 2 + gw], tag); }
      }
      for (int e4 = blockIdx.x * 96 + gt; e4 < EE / 4; e4 += NCTA * 96) {
        const int4 s4 = __ldg((const int4*)esrc + e4), d4 = __ldg((const int4*)edst + e4);
        const int s[4] = {s4.x, s4.y, s4.z, s4.w}, d[4] = {d4.x, d4.y, d4.z, d4.w};
        int slot[4];
#pragma unroll
        for (int k = 0; k < 4; k++) slot[k] = atomicAdd(&g_cnt[d[k]], 1);
#pragma unroll
        for (int k = 0; k < 4; k++) {
          if (slot[k] < CAP) g_ell[d[k] * CAP + slot[k]] = (uint16_t)s[k];
          else g_ovf_next[e4 * 4 + k] = atomicExch(&g_ovf_head[d[k]], e4 * 4 + k);
        }
      }
      bar_sync(5, 96);
      if (gt == 0) {
        __threadfence();
        atomicAdd(&g_ellctr, 1ull);
        int it = 0; unsigned long long v;
        do { asm volatile("ld.acquire.gpu.global.u64 %0, [%1];" : "=l"(v) : "l"(&g_ellctr) : "memory"); if (v >= epoch * NCTA) break; __nanosleep(200); } while (++it < SPIN);
      }
      bar_sync(5, 96);
      if (gw == 0) PROBE1(2);
      const int lr0 = isY ? 0 : 64;
      const int row0 = qfin * 128 + (isY ? 0 : rank * 64) - lr0;
      const uint2* x2 = (const uint2*)x;
      int lr = lr0 + gw;
      int n_nx = __ldcg(&g_cnt[row0 + lr]), i_nx = __ldcg(&g_ell[(row0 + lr) * CAP + lane]);
      for (; lr < 128; lr += 3) {
        const int row = row0 + lr, n = n_nx;
        const int nell = min(n, CAP);
        const int idx = lane < nell ? i_nx : 0;
        if (lr + 3 < 128) { n_nx = __ldcg(&g_cnt[row + 3]); i_nx = __ldcg(&g_ell[(row + 3) * CAP + lane]); }
        float2 stt = __ldcg(&g_stats[idx]);
        if (lane >= nell) stt = make_float2(0.f, 0.f);
        const float di = row < NN ? __bfloat162float(deg_inv[row]) : 0.f;
        float a0 = 0.f, a1 = 0.f, a2 = 0.f, a3 = 0.f;
        for (int e = 0; e < nell; e += 8) {
          uint2 v[8];
#pragma unroll
          for (int k = 0; k < 8; k++) v[k] = __ldg(x2 + __shfl_sync(~0u, idx, e + k) * 32 + lane);
#pragma unroll
          for (int k = 0; k < 8; k++) {
            const float a = __shfl_sync(~0u, stt.x, e + k);
            a0 = fmaf(bf_lo(v[k].x), a, a0); a1 = fmaf(bf_hi(v[k].x), a, a1); a2 = fmaf(bf_lo(v[k].y), a, a2); a3 = fmaf(bf_hi(v[k].y), a, a3);
          }
        }
        float b = stt.y;
#pragma unroll
        for (int o = 16; o; o >>= 1) b += __shfl_xor_sync(~0u, b, o);
        if (n > CAP) {
          int e = __ldcg(&g_ovf_head[row]);
          for (int k = CAP; k < n; k++) {
            const int s = __ldg(esrc + e);
            const float2 sv = __ldcg(&g_stats[s]);
            const uint2 v = __ldg(x2 + s * 32 + lane);
            a0 = fmaf(bf_lo(v.x), sv.x, a0); a1 = fmaf(bf_hi(v.x), sv.x, a1); a2 = fmaf(bf_lo(v.y), sv.x, a2); a3 = fmaf(bf_hi(v.y), sv.x, a3);
            b += sv.y;
            e = __ldcg(&g_ovf_next[e]);
          }
        }
        if (lane == 0) g_cnt[row] = 0;
        asm volatile("st.shared.v2.b32 [%0], {%1, %2};" :: "r"(sb + SM_G + tile_off(lr, lane >> 1) + (lane & 1) * 8),
                     "r"(pack_bf16((a0 - b) * di, (a1 - b) * di)), "r"(pack_bf16((a2 - b) * di, (a3 - b) * di)) : "memory");
      }
      fence_async();
      mbar_arrive(bars + 8 * B_G);
      if (gw == 0) PROBE1(3);
      if (isX1 && gw < 2) {
        bar_sync(6 + gw, 160);
        if (lane == 0) { __threadfence(); st_rel(&g_pflag[grp * 4 + (cl & 1) * 2 + gw], tag); }
      }
      if (isY) {
        if (lane < 4) wait_flag(&g_pflag[grp * 4 + lane], tag);
        __syncwarp();
        for (int u = gt; u < 256; u += 96) {
          const int w = u >> 7, tt = u & 127;
          const uint8_t* pa = g_part + (grp * 4 + w) * PART_B;
          const uint8_t* pb = pa + 2 * PART_B;
          const float2 la = __ldcg((const float2*)(pa + 16384) + tt), lb = __ldcg((const float2*)(pb + 16384) + tt);
          const float x0 = fmaxf(la.x, lb.x), x1 = fmaxf(la.y, lb.y);
          const float wb0 = ex2(lb.x - x0), wb1 = ex2(lb.y - x1);
          const float s0 = ex2(la.x - x0) + wb0, s1 = ex2(la.y - x1) + wb1;
          const float f0 = wb0 / s0, f1 = wb1 / s1;
          asm volatile("st.shared.v2.f32 [%0], {%1, %2};" :: "r"(sb + SM_LAM + u * 8), "f"(x0 + lg2(s0)), "f"(x1 + lg2(s1)) : "memory");
#pragma unroll 2
          for (int k = 0; k < 8; k++) {
            const uint4 a = __ldcg((const uint4*)(pa + k * 2048) + tt), b = __ldcg((const uint4*)(pb + k * 2048) + tt);
            auto mix = [](uint32_t p, uint32_t q, float f) { const float pl = h_lo(p), phh = h_hi(p); return pack_f16(fmaf(h_lo(q) - pl, f, pl), fmaf(h_hi(q) - phh, f, phh)); };
            asm volatile("st.shared.v4.b32 [%0], {%1, %2, %3, %4};" :: "r"(sb + SM_M + w * 16384 + k * 2048 + tt * 16),
                         "r"(mix(a.x, b.x, f0)), "r"(mix(a.y, b.y, f1)), "r"(mix(a.z, b.z, f0)), "r"(mix(a.w, b.w, f1)) : "memory");
          }
        }
        mbar_arrive(bars + 8 * B_M);
        if (gw == 0) PROBE1(4);
      }
    }
  } else {
    asm volatile("setmaxnreg.inc.sync.aligned.u32 232;");
    const int t = tid & 127, q = lane & 3, rr = lane >> 2;
    const int blk_fin = isY ? wg : wg ^ 1 ^ rank;
    float O[64], S[T / 2];
    uint32_t P[T / 4], Q[32];
    {
      const int r0 = (isX1 ? (3 * grp + 1) * 128 + wg * 64 : qfin * 128 + blk_fin * 64) + (t >> 5) * 16 + rr;
      uint4 xv[8];
#pragma unroll
      for (int i = 0; i < 8; i++) {
        const int r = r0 + (i >> 2) * 8;
        xv[i] = r < NN ? __ldg((const uint4*)x + r * 16 + (i & 3) * 4 + q) : make_uint4(0, 0, 0, 0);
      }
      bar_sync(0, 384);
      asm volatile("barrier.cluster.arrive.release.aligned;" ::: "memory");
#pragma unroll
      for (int h = 0; h < 2; h++) {
        const int r = r0 + h * 8;
        float v[32];
#pragma unroll
        for (int i = 0; i < 4; i++) {
          const uint4 u = xv[h * 4 + i];
          v[8 * i] = bf_lo(u.x); v[8 * i + 1] = bf_hi(u.x); v[8 * i + 2] = bf_lo(u.y); v[8 * i + 3] = bf_hi(u.y);
          v[8 * i + 4] = bf_lo(u.z); v[8 * i + 5] = bf_hi(u.z); v[8 * i + 6] = bf_lo(u.w); v[8 * i + 7] = bf_hi(u.w);
        }
        float s0 = 0.f, s1 = 0.f, s2 = 0.f, s3 = 0.f;
#pragma unroll
        for (int i = 0; i < 8; i++) { s0 += v[4 * i]; s1 += v[4 * i + 1]; s2 += v[4 * i + 2]; s3 += v[4 * i + 3]; }
        const float mean = quad_sum((s0 + s1) + (s2 + s3)) * (1.f / 128.f);
        s0 = s1 = s2 = s3 = 0.f;
#pragma unroll
        for (int i = 0; i < 32; i++) v[i] -= mean;
#pragma unroll
        for (int i = 0; i < 8; i++) { s0 = fmaf(v[4 * i], v[4 * i], s0); s1 = fmaf(v[4 * i + 1], v[4 * i + 1], s1); s2 = fmaf(v[4 * i + 2], v[4 * i + 2], s2); s3 = fmaf(v[4 * i + 3], v[4 * i + 3], s3); }
        const float rstd = rsqrtf(quad_sum((s0 + s1) + (s2 + s3)) * (1.f / 128.f) + 1e-5f);
        if (writes_h) {
          const float cc = r < NN ? COFF : 0.f;
          const float off = fmaf(__shfl_sync(~0u, v[31], lane | 3) * rstd, RS1, cc);
#pragma unroll
          for (int i = 0; i < 4; i++) {
            uint4 o;
            o.x = pack_f16(fmaf(v[8 * i], rstd, off), fmaf(v[8 * i + 1], rstd, off));
            o.y = pack_f16(fmaf(v[8 * i + 2], rstd, off), fmaf(v[8 * i + 3], rstd, off));
            o.z = pack_f16(fmaf(v[8 * i + 4], rstd, off), fmaf(v[8 * i + 5], rstd, off));
            o.w = pack_f16(fmaf(v[8 * i + 6], rstd, off), (i == 3 && q == 3) ? cc : fmaf(v[8 * i + 7], rstd, off));
            *(uint4*)(g_h + tile_off(r, 4 * i + q)) = o;
          }
          if (q == 0) g_stats[r] = make_float2(rstd, mean * rstd);
        }
#pragma unroll
        for (int ks = 0; ks < 8; ks++) {
          Q[4 * ks + h] = pack_bf16(v[4 * ks] * rstd, v[4 * ks + 1] * rstd);
          Q[4 * ks + 2 + h] = pack_bf16(v[4 * ks + 2] * rstd, v[4 * ks + 3] * rstd);
        }
      }
      if (writes_h) bar_arrive(3 + wg, 160);
      PROBE(5 + wg);
      mbar_wait(bars + 8 * B_WQ, 0);
      wg_fence();
#pragma unroll
      for (int ks = 0; ks < 8; ks++) mma_rs_t(O, Q[4 * ks], Q[4 * ks + 1], Q[4 * ks + 2], Q[4 * ks + 3], desc_mn(sb + SM_KV + 2 * TILE_B) + ks * 256, ks > 0);
      wg_commit(); wg_wait<0>(); pin(O); pin(Q);
#pragma unroll
      for (int i = 0; i < 32; i++) Q[i] = pack_bf16(O[2 * i], O[2 * i + 1]);
      mbar_wait(bars + 8 * B_WK, 0);
      pin(Q); wg_fence();
#pragma unroll
      for (int ks = 0; ks < 8; ks++) mma_rs(O, Q[4 * ks], Q[4 * ks + 1], Q[4 * ks + 2], Q[4 * ks + 3], desc_k(sb + SM_KV + 3 * TILE_B) + koff(ks), ks > 0);
      wg_commit(); wg_wait<0>(); pin(O); pin(Q);
      if (t == 0) mbar_arrive(bars + 8 * B_WFREE);
      auto rot_adj = [&](int h) {
        float s0 = 0.f, s1 = 0.f;
#pragma unroll
        for (int i = 0; i < 16; i++) { s0 += O[4 * i + 2 * h]; s1 += O[4 * i + 2 * h + 1]; }
        return (quad_sum(s0 + s1) * RSN - __shfl_sync(~0u, O[61 + 2 * h], lane | 3)) * RS1;
      };
      {
        const float j0 = -rot_adj(0) * QSCALE, j1 = -rot_adj(1) * QSCALE;
#pragma unroll
        for (int i = 0; i < 16; i++) {
          Q[2 * i] = pack_f16_sat(fmaf(O[4 * i], QSCALE, j0), fmaf(O[4 * i + 1], QSCALE, j0));
          Q[2 * i + 1] = pack_f16_sat(fmaf(O[4 * i + 2], QSCALE, j1), fmaf(O[4 * i + 3], QSCALE, j1));
        }
        if (q == 3) { Q[30] &= 0xffffu; Q[31] &= 0xffffu; }
      }
      if (isZ) {
        mbar_wait(bars + 8 * B_WZ, 0);
        wg_fence();
#pragma unroll
        for (int ks = 0; ks < 8; ks++) mma_ss_ta(O, desc_mn(sb + SM_G + wg * 1024) + ks * 256, desc_k(sb + SM_M) + koff(ks), ks > 0);
        wg_commit(); wg_wait<0>(); pin(O);
        const float j0 = rank ? rot_adj(0) : 0.f, j1 = rank ? rot_adj(1) : 0.f;
#pragma unroll
        for (int h = 0; h < 2; h++) {
          const int e = wg * 64 + (t >> 5) * 16 + rr + h * 8;
          const int n = 8 * (4 * (e >> 5) + ((e >> 1) & 3)) + 2 * ((e >> 3) & 3) + (e & 1);
          const float j = h ? j1 : j0;
#pragma unroll
          for (int i = 0; i < 16; i++) {
            uint32_t u = pack_bf16(O[4 * i + 2 * h] - j, O[4 * i + 2 * h + 1] - j);
            if (i == 15 && q == 3 && rank) u &= 0xffffu;
            *(uint32_t*)(g_wc + rank * 32768 + tile_off(n, i) + q * 4) = u;
          }
        }
        bar_arrive(6 + wg, 160);
      }
      asm volatile("barrier.cluster.wait.acquire.aligned;" ::: "memory");
    }
    PROBE(7 + wg);

    float m0 = -3e38f, m1 = -3e38f;
    bool sticky = false;
    int accz = 0;
    auto issue_qk = [&](int st) {
      const uint64_t d = desc_k(sb + SM_KV + st * TILE_B);
#pragma unroll
      for (int ks = 0; ks < 8; ks++) mma_qk(S, Q[4 * ks], Q[4 * ks + 1], Q[4 * ks + 2], Q[4 * ks + 3], d + koff(ks), ks > 0);
    };
    auto issue_pv = [&](int st) {
      const uint64_t d = desc_mn(sb + SM_KV + st * TILE_B);
#pragma unroll
      for (int ks = 0; ks < T / 16; ks++) mma_pv(O, P[4 * ks], P[4 * ks + 1], P[4 * ks + 2], P[4 * ks + 3], d + ks * 256, ks > 0 ? 1 : accz);
    };
    auto exact = [&]() {
      const float q0 = h_hi(__shfl_sync(~0u, Q[30], lane | 3)), q1 = h_hi(__shfl_sync(~0u, Q[31], lane | 3));
      float x0 = fmaf(COFF, q0, m0), x1 = fmaf(COFF, q1, m1);
#pragma unroll
      for (int i = 0; i < T / 8; i++) { x0 = fmaxf(x0, fmaxf(S[4 * i], S[4 * i + 1])); x1 = fmaxf(x1, fmaxf(S[4 * i + 2], S[4 * i + 3])); }
      x0 = quad_max(x0); x1 = quad_max(x1);
      const __half n0 = __float2half_ru(fminf(fmaxf(fmaf(x0, -1.f / COFF, q0), -65504.f), 65504.f));
      const __half n1 = __float2half_ru(fminf(fmaxf(fmaf(x1, -1.f / COFF, q1), -65504.f), 65504.f));
      const float d0e = COFF * (q0 - __half2float(n0)), d1e = COFF * (q1 - __half2float(n1));
      const bool k0 = fabsf(x0 - d0e) > 1.f, k1 = fabsf(x1 - d1e) > 1.f;
      const float d0 = k0 ? x0 : d0e, d1 = k1 ? x1 : d1e;
      const float r0 = k0 ? fmaf(-COFF, q0, x0) : -COFF * __half2float(n0), r1 = k1 ? fmaf(-COFF, q1, x1) : -COFF * __half2float(n1);
      sticky = __any_sync(~0u, k0 || k1);
      if (accz) {
        const float a0 = ex2(m0 - r0), a1 = ex2(m1 - r1);
#pragma unroll
        for (int i = 0; i < 16; i++) { O[4 * i] *= a0; O[4 * i + 1] *= a0; O[4 * i + 2] *= a1; O[4 * i + 3] *= a1; }
      }
      m0 = r0; m1 = r1;
      if (q == 3) { Q[30] = (Q[30] & 0xffffu) | ((uint32_t)__half_as_ushort(n0) << 16); Q[31] = (Q[31] & 0xffffu) | ((uint32_t)__half_as_ushort(n1) << 16); }
#pragma unroll
      for (int i = 0; i < T / 8; i++) {
        P[2 * i] = pack_f16(ex2(S[4 * i] - d0), ex2(S[4 * i + 1] - d0));
        P[2 * i + 1] = pack_f16(ex2(S[4 * i + 2] - d1), ex2(S[4 * i + 3] - d1));
      }
    };
    auto fast = [&]() -> bool {
      uint32_t acc = 0;
#pragma unroll
      for (int i = 0; i < T / 8; i++) {
        P[2 * i] = pack_f16(ex2(S[4 * i]), ex2(S[4 * i + 1]));
        P[2 * i + 1] = pack_f16(ex2(S[4 * i + 2]), ex2(S[4 * i + 3]));
        asm("fma.rn.f16x2 %0, %1, %2, %0;" : "+r"(acc) : "r"(P[2 * i]), "r"(P[2 * i + 1]));
      }
      return __any_sync(~0u, (((acc & 0x7c007c00u) + 0x04000400u) & 0x80008000u) != 0);
    };
    float L0, L1;
    auto getL = [&]() { L0 = __shfl_sync(~0u, O[61], lane | 3); L1 = __shfl_sync(~0u, O[63], lane | 3); };
    auto norm_chunk = [&](int k, float i0, float c0, float i1, float c1) {
      return make_uint4(pack_f16(fmaf(O[8 * k], i0, c0), fmaf(O[8 * k + 1], i0, c0)), pack_f16(fmaf(O[8 * k + 2], i1, c1), fmaf(O[8 * k + 3], i1, c1)),
                        pack_f16(fmaf(O[8 * k + 4], i0, c0), fmaf(O[8 * k + 5], i0, c0)), pack_f16(fmaf(O[8 * k + 6], i1, c1), fmaf(O[8 * k + 7], i1, c1)));
    };

    if (wg == 1) bar_arrive(1, 256);
    int st = 0, ph = 0;
    mbar_wait(bars + 8 * B_FULL, 0);
    PROBE(9 + wg);
    bar_sync(1 + wg, 256);
    pin(Q); wg_fence();
    issue_qk(0);
    wg_commit();
    bar_arrive(2 - wg, 256);
    wg_wait<0>(); pin(S); pin(Q);
    exact();
    if (isX0) {
      const uint32_t dq = mapa(sb + (wg ? SM_G : SM_M) + t * 16, 1);
#pragma unroll
      for (int k = 0; k < 8; k++) st_cl4(dq + k * 2048, Q[4 * k], Q[4 * k + 1], Q[4 * k + 2], Q[4 * k + 3]);
      st_cl2(mapa(sb + SM_M2 + (wg ^ 1) * 1024 + t * 8, 1), m0, m1);
      mbar_arrive_remote(mapa(bars + 8 * B_Q2, 1));
    }
    for (int j = 1; j < ntiles; j++) {
      const int pst = st;
      if (++st == NST) { st = 0; ph ^= 1; }
      if (j == jsw) {
        mbar_wait_cluster(bars + 8 * B_Q2, 0);
#pragma unroll
        for (int k = 0; k < 8; k++) { const uint4 v = lds4(sb + (wg ? SM_M : SM_G) + k * 2048 + t * 16); Q[4 * k] = v.x; Q[4 * k + 1] = v.y; Q[4 * k + 2] = v.z; Q[4 * k + 3] = v.w; }
      }
      mbar_wait(bars + 8 * (B_FULL + st), ph);
      bar_sync(1 + wg, 256);
      pin(S); pin(O); pin(P); pin(Q); wg_fence();
      issue_pv(pst);
      issue_qk(st);
      wg_commit();
      bar_arrive(2 - wg, 256);
      wg_wait<0>(); pin(S); pin(O); pin(P); pin(Q);
      if (t == 0) mbar_arrive(bars + 8 * (B_EMPTY + pst));
      accz = 1;
      if (j == jsw) {
        getL();
        uint8_t* dst = g_part + (grp * 4 + (cl & 1) * 2 + wg) * PART_B;
        const float i0 = COFF / L0, i1 = COFF / L1;
#pragma unroll
        for (int k = 0; k < 8; k++) *(uint4*)(dst + k * 2048 + t * 16) = norm_chunk(k, i0, -COFF, i1, -COFF);
        *(float2*)(dst + 16384 + t * 8) = make_float2(m0 + lg2(L0), m1 + lg2(L1));
        bar_arrive(6 + wg, 160);
        const float2 mm = lds2(sb + SM_M2 + wg * 1024 + t * 8);
        m0 = mm.x; m1 = mm.y;
        const float q0 = h_hi(__shfl_sync(~0u, Q[30], lane | 3)), q1 = h_hi(__shfl_sync(~0u, Q[31], lane | 3));
        sticky = __any_sync(~0u, m0 != -COFF * q0 || m1 != -COFF * q1);
        accz = 0;
      }
      if (sticky || fast()) exact();
    }
    PROBE(11 + wg);
    const bool finisher = isY || wg == 1;
    if (!finisher) {
      bar_sync(1 + wg, 256);
      pin(O); pin(P); wg_fence();
      issue_pv(st);
      wg_commit();
      bar_arrive(2, 256);
      wg_wait<0>(); pin(O);
      getL();
      const float i0 = L0 > 0.f ? COFF / L0 : 0.f, i1 = L1 > 0.f ? COFF / L1 : 0.f;
      const float c0 = L0 > 0.f ? -COFF : 0.f, c1 = L1 > 0.f ? -COFF : 0.f;
      const uint32_t dm = mapa(sb + SM_M + 16384 + t * 16, rank ^ 1);
#pragma unroll
      for (int k = 0; k < 8; k++) { const uint4 v = norm_chunk(k, i0, c0, i1, c1); st_cl4(dm + k * 2048, v.x, v.y, v.z, v.w); }
      st_cl2(mapa(sb + SM_LAM + 1024 + t * 8, rank ^ 1), m0 + lg2(L0), m1 + lg2(L1));
      mbar_arrive_remote(mapa(bars + 8 * B_M, rank ^ 1));
      PROBE(13);
    } else {
      float Y[64];
      const int r0 = qfin * 128 + blk_fin * 64 + (t >> 5) * 16 + rr;
      uint4 xv[8];
#pragma unroll
      for (int i = 0; i < 8; i++) {
        const int r = r0 + (i >> 2) * 8;
        xv[i] = r < NN ? __ldg((const uint4*)x + r * 16 + (i & 3) * 4 + q) : make_uint4(0, 0, 0, 0);
      }
      int s1 = st + 1, p1 = ph; if (s1 == NST) { s1 = 0; p1 ^= 1; }
      int s2 = s1 + 1, p2 = p1; if (s2 == NST) { s2 = 0; p2 ^= 1; }
      mbar_wait(bars + 8 * B_G, 0);
      mbar_wait(bars + 8 * (B_FULL + s1), p1);
      bar_sync(1 + wg, 256);
      pin(O); pin(P); wg_fence();
      issue_pv(st);
      wg_commit();
#pragma unroll
      for (int ks = 0; ks < 8; ks++) mma_ss(Y, desc_k(sb + SM_G + wg * 16384) + koff(ks), desc_k(sb + SM_KV + s1 * TILE_B) + koff(ks), ks > 0);
      wg_commit();
      if (wg == 0) bar_arrive(2, 256);
      mbar_wait(bars + 8 * (B_FULL + s2), p2);
      mbar_wait_cluster(bars + 8 * B_M, 0);
      const float2 lo = lds2(sb + SM_LAM + wg * 1024 + t * 8);
      wg_wait<1>(); pin(O); pin(P);
      PROBE(14 + wg);
      getL();
      const float w0 = 1.f / (1.f + ex2(lo.x - m0 - lg2(L0))), w1 = 1.f / (1.f + ex2(lo.y - m1 - lg2(L1)));
      const float i0 = L0 > 0.f ? w0 * COFF / L0 : 0.f, i1 = L1 > 0.f ? w1 * COFF / L1 : 0.f;
      const float c0 = -COFF * w0, c1 = -COFF * w1, b0 = 1.f - w0, b1 = 1.f - w1;
#pragma unroll
      for (int k = 0; k < 8; k++) {
        const uint4 v = lds4(sb + SM_M + wg * 16384 + k * 2048 + t * 16);
        P[4 * k] = pack_bf16(fmaf(h_lo(v.x), b0, fmaf(O[8 * k], i0, c0)), fmaf(h_hi(v.x), b0, fmaf(O[8 * k + 1], i0, c0)));
        P[4 * k + 1] = pack_bf16(fmaf(h_lo(v.y), b1, fmaf(O[8 * k + 2], i1, c1)), fmaf(h_hi(v.y), b1, fmaf(O[8 * k + 3], i1, c1)));
        P[4 * k + 2] = pack_bf16(fmaf(h_lo(v.z), b0, fmaf(O[8 * k + 4], i0, c0)), fmaf(h_hi(v.z), b0, fmaf(O[8 * k + 5], i0, c0)));
        P[4 * k + 3] = pack_bf16(fmaf(h_lo(v.w), b1, fmaf(O[8 * k + 6], i1, c1)), fmaf(h_hi(v.w), b1, fmaf(O[8 * k + 7], i1, c1)));
      }
      pin(P); wg_fence();
#pragma unroll
      for (int ks = 0; ks < 8; ks++) mma_rs(Y, P[4 * ks], P[4 * ks + 1], P[4 * ks + 2], P[4 * ks + 3], desc_k(sb + SM_KV + s2 * TILE_B) + koff(ks), 1);
      wg_commit(); wg_wait<0>(); pin(Y);
#pragma unroll
      for (int i = 0; i < 8; i++) {
        const int h = i >> 2, I = i & 3, r = r0 + h * 8;
        const uint4 u = xv[i];
        uint4 o;
        o.x = pack_bf16(bf_lo(u.x) + Y[16 * I + 2 * h], bf_hi(u.x) + Y[16 * I + 2 * h + 1]);
        o.y = pack_bf16(bf_lo(u.y) + Y[16 * I + 4 + 2 * h], bf_hi(u.y) + Y[16 * I + 4 + 2 * h + 1]);
        o.z = pack_bf16(bf_lo(u.z) + Y[16 * I + 8 + 2 * h], bf_hi(u.z) + Y[16 * I + 8 + 2 * h + 1]);
        o.w = pack_bf16(bf_lo(u.w) + Y[16 * I + 12 + 2 * h], bf_hi(u.w) + Y[16 * I + 12 + 2 * h + 1]);
        if (r < NN) *((uint4*)out + r * 16 + I * 4 + q) = o;
      }
      PROBE(16 + wg);
    }
  }
}

}

extern "C" void kernel_launch(void* const* d_in, const int* in_sizes, int n_in, void* d_out, int out_size) {
  (void)in_sizes; (void)n_in; (void)out_size;
  cudaFuncSetAttribute(graphgps_kernel, cudaFuncAttributeMaxDynamicSharedMemorySize, SM_TOTAL);
  graphgps_kernel<<<NCTA, 384, SM_TOTAL>>>(
      (const __nv_bfloat16*)d_in[0], (const int*)d_in[1], (const int*)d_in[2], (const __nv_bfloat16*)d_in[3],
      (const __nv_bfloat16*)d_in[4], (const __nv_bfloat16*)d_in[5], (const __nv_bfloat16*)d_in[6],
      (const __nv_bfloat16*)d_in[7], (const __nv_bfloat16*)d_in[8], (__nv_bfloat16*)d_out);
}
```

```cpp
#include <cuda_runtime.h>
#include <cuda_bf16.h>
#include <cuda_fp16.h>
#include <stdint.h>

namespace {

constexpr int NN = 10000;
constexpr int EE = 160000;
constexpr int NPAD = 10112;
constexpr int T = 144;
constexpr int NST = 4;
constexpr uint32_t TILE_B = T * 256;
constexpr int CAP = 32;
constexpr int NCTA = 132;
constexpr float COFF = 10.f;
constexpr float RS1 = 0.09695833f;
constexpr float RSN = 0.08838835f;
constexpr float QSCALE = 0.12751744f;
constexpr int SPIN = 1 << 20;

constexpr uint32_t SM_KV = 0;
constexpr uint32_t SM_G = NST * TILE_B;
constexpr uint32_t SM_M = SM_G + 32768;
constexpr uint32_t SM_LAM = SM_M + 32768;
constexpr uint32_t SM_M2 = SM_LAM + 2048;
constexpr uint32_t SM_BAR = SM_M2 + 2048;
constexpr uint32_t SM_TOTAL = SM_BAR + 512 + 1024;
enum { B_FULL = 0, B_EMPTY = NST, B_WQ = 2 * NST, B_WK, B_WZ, B_WFREE, B_G, B_M, B_Q2, B_S0, B_TAG };

constexpr int PART_B = 16384 + 1024;

__device__ __align__(1024) uint8_t g_h[NPAD * 256];
__device__ __align__(1024) uint8_t g_hp[(NPAD + 1) * 256];
__device__ int g_cnt[NPAD];
__device__ __align__(128) uint32_t g_ell[NPAD * CAP];
__device__ int g_ovf_head[NPAD];
__device__ int g_ovf_next[EE];
__device__ __align__(1024) uint8_t g_part[26 * 2 * 2 * PART_B];
__device__ __align__(1024) uint8_t g_wc[2 * 32768];
__device__ unsigned g_hflag[96];
__device__ unsigned g_pflag[26 * 4];
__device__ unsigned g_wflag[4];
__device__ unsigned long long g_ticket;
__device__ unsigned long long g_ellctr;
#define PROBE(k)
#define PROBE1(k)

__device__ __forceinline__ void mma_qk(float (&d)[72], uint32_t a0, uint32_t a1, uint32_t a2, uint32_t a3, uint64_t db, int scale_d) {
  asm volatile("{\n.reg .pred p;\nsetp.ne.b32 p, %77, 0;\n"
    "wgmma.mma_async.sync.aligned.m64n144k16.f32.f16.f16 {"
    "%0, %1, %2, %3, %4, %5, %6, %7, %8, %9, %10, %11, %12, %13, %14, %15, "
    "%16, %17, %18, %19, %20, %21, %22, %23, %24, %25, %26, %27, %28, %29, %30, %31, "
    "%32, %33, %34, %35, %36, %37, %38, %39, %40, %41, %42, %43, %44, %45, %46, %47, "
    "%48, %49, %50, %51, %52, %53, %54, %55, %56, %57, %58, %59, %60, %61, %62, %63, "
    "%64, %65, %66, %67, %68, %69, %70, %71}, "
    "{%72, %73, %74, %75}, %76, p, 1, 1, 0;\n}\n"
    : "+f"(d[0]), "+f"(d[1]), "+f"(d[2]), "+f"(d[3]), "+f"(d[4]), "+f"(d[5]), "+f"(d[6]), "+f"(d[7]),
      "+f"(d[8]), "+f"(d[9]), "+f"(d[10]), "+f"(d[11]), "+f"(d[12]), "+f"(d[13]), "+f"(d[14]), "+f"(d[15]),
      "+f"(d[16]), "+f"(d[17]), "+f"(d[18]), "+f"(d[19]), "+f"(d[20]), "+f"(d[21]), "+f"(d[22]), "+f"(d[23]),
      "+f"(d[24]), "+f"(d[25]), "+f"(d[26]), "+f"(d[27]), "+f"(d[28]), "+f"(d[29]), "+f"(d[30]), "+f"(d[31]),
      "+f"(d[32]), "+f"(d[33]), "+f"(d[34]), "+f"(d[35]), "+f"(d[36]), "+f"(d[37]), "+f"(d[38]), "+f"(d[39]),
      "+f"(d[40]), "+f"(d[41]), "+f"(d[42]), "+f"(d[43]), "+f"(d[44]), "+f"(d[45]), "+f"(d[46]), "+f"(d[47]),
      "+f"(d[48]), "+f"(d[49]), "+f"(d[50]), "+f"(d[51]), "+f"(d[52]), "+f"(d[53]), "+f"(d[54]), "+f"(d[55]),
      "+f"(d[56]), "+f"(d[57]), "+f"(d[58]), "+f"(d[59]), "+f"(d[60]), "+f"(d[61]), "+f"(d[62]), "+f"(d[63]),
      "+f"(d[64]), "+f"(d[65]), "+f"(d[66]), "+f"(d[67]), "+f"(d[68]), "+f"(d[69]), "+f"(d[70]), "+f"(d[71])
    : "r"(a0), "r"(a1), "r"(a2), "r"(a3), "l"(db), "r"(scale_d));
}
__device__ __forceinline__ void mma_qk0(float (&d)[64], uint32_t a0, uint32_t a1, uint32_t a2, uint32_t a3, uint64_t db, int scale_d) {
  asm volatile("{\n.reg .pred p;\nsetp.ne.b32 p, %69, 0;\n"
    "wgmma.mma_async.sync.aligned.m64n128k16.f32.f16.f16 {"
    "%0, %1, %2, %3, %4, %5, %6, %7, %8, %9, %10, %11, %12, %13, %14, %15, "
    "%16, %17, %18, %19, %20, %21, %22, %23, %24, %25, %26, %27, %28, %29, %30, %31, "
    "%32, %33, %34, %35, %36, %37, %38, %39, %40, %41, %42, %43, %44, %45, %46, %47, "
    "%48, %49, %50, %51, %52, %53, %54, %55, %56, %57, %58, %59, %60, %61, %62, %63}, "
    "{%64, %65, %66, %67}, %68, p, 1, 1, 0;\n}\n"
    : "+f"(d[0]), "+f"(d[1]), "+f"(d[2]), "+f"(d[3]), "+f"(d[4]), "+f"(d[5]), "+f"(d[6]), "+f"(d[7]),
      "+f"(d[8]), "+f"(d[9]), "+f"(d[10]), "+f"(d[11]), "+f"(d[12]), "+f"(d[13]), "+f"(d[14]), "+f"(d[15]),
      "+f"(d[16]), "+f"(d[17]), "+f"(d[18]), "+f"(d[19]), "+f"(d[20]), "+f"(d[21]), "+f"(d[22]), "+f"(d[23]),
      "+f"(d[24]), "+f"(d[25]), "+f"(d[26]), "+f"(d[27]), "+f"(d[28]), "+f"(d[29]), "+f"(d[30]), "+f"(d[31]),
      "+f"(d[32]), "+f"(d[33]), "+f"(d[34]), "+f"(d[35]), "+f"(d[36]), "+f"(d[37]), "+f"(d[38]), "+f"(d[39]),
      "+f"(d[40]), "+f"(d[41]), "+f"(d[42]), "+f"(d[43]), "+f"(d[44]), "+f"(d[45]), "+f"(d[46]), "+f"(d[47]),
      "+f"(d[48]), "+f"(d[49]), "+f"(d[50]), "+f"(d[51]), "+f"(d[52]), "+f"(d[53]), "+f"(d[54]), "+f"(d[55]),
      "+f"(d[56]), "+f"(d[57]), "+f"(d[58]), "+f"(d[59]), "+f"(d[60]), "+f"(d[61]), "+f"(d[62]), "+f"(d[63])
    : "r"(a0), "r"(a1), "r"(a2), "r"(a3), "l"(db), "r"(scale_d));
}
__device__ __forceinline__ void mma_pv(float (&d)[64], uint32_t a0, uint32_t a1, uint32_t a2, uint32_t a3, uint64_t db, int scale_d) {
  asm volatile("{\n.reg .pred p;\nsetp.ne.b32 p, %69, 0;\n"
    "wgmma.mma_async.sync.aligned.m64n128k16.f32.f16.f16 {"
    "%0, %1, %2, %3, %4, %5, %6, %7, %8, %9, %10, %11, %12, %13, %14, %15, "
    "%16, %17, %18, %19, %20, %21, %22, %23, %24, %25, %26, %27, %28, %29, %30, %31, "
    "%32, %33, %34, %35, %36, %37, %38, %39, %40, %41, %42, %43, %44, %45, %46, %47, "
    "%48, %49, %50, %51, %52, %53, %54, %55, %56, %57, %58, %59, %60, %61, %62, %63}, "
    "{%64, %65, %66, %67}, %68, p, 1, 1, 1;\n}\n"
    : "+f"(d[0]), "+f"(d[1]), "+f"(d[2]), "+f"(d[3]), "+f"(d[4]), "+f"(d[5]), "+f"(d[6]), "+f"(d[7]),
      "+f"(d[8]), "+f"(d[9]), "+f"(d[10]), "+f"(d[11]), "+f"(d[12]), "+f"(d[13]), "+f"(d[14]), "+f"(d[15]),
      "+f"(d[16]), "+f"(d[17]), "+f"(d[18]), "+f"(d[19]), "+f"(d[20]), "+f"(d[21]), "+f"(d[22]), "+f"(d[23]),
      "+f"(d[24]), "+f"(d[25]), "+f"(d[26]), "+f"(d[27]), "+f"(d[28]), "+f"(d[29]), "+f"(d[30]), "+f"(d[31]),
      "+f"(d[32]), "+f"(d[33]), "+f"(d[34]), "+f"(d[35]), "+f"(d[36]), "+f"(d[37]), "+f"(d[38]), "+f"(d[39]),
      "+f"(d[40]), "+f"(d[41]), "+f"(d[42]), "+f"(d[43]), "+f"(d[44]), "+f"(d[45]), "+f"(d[46]), "+f"(d[47]),
      "+f"(d[48]), "+f"(d[49]), "+f"(d[50]), "+f"(d[51]), "+f"(d[52]), "+f"(d[53]), "+f"(d[54]), "+f"(d[55]),
      "+f"(d[56]), "+f"(d[57]), "+f"(d[58]), "+f"(d[59]), "+f"(d[60]), "+f"(d[61]), "+f"(d[62]), "+f"(d[63])
    : "r"(a0), "r"(a1), "r"(a2), "r"(a3), "l"(db), "r"(scale_d));
}
__device__ __forceinline__ void mma_rs_t(float (&d)[64], uint32_t a0, uint32_t a1, uint32_t a2, uint32_t a3, uint64_t db, int scale_d) {
  asm volatile("{\n.reg .pred p;\nsetp.ne.b32 p, %69, 0;\n"
    "wgmma.mma_async.sync.aligned.m64n128k16.f32.bf16.bf16 {"
    "%0, %1, %2, %3, %4, %5, %6, %7, %8, %9, %10, %11, %12, %13, %14, %15, "
    "%16, %17, %18, %19, %20, %21, %22, %23, %24, %25, %26, %27, %28, %29, %30, %31, "
    "%32, %33, %34, %35, %36, %37, %38, %39, %40, %41, %42, %43, %44, %45, %46, %47, "
    "%48, %49, %50, %51, %52, %53, %54, %55, %56, %57, %58, %59, %60, %61, %62, %63}, "
    "{%64, %65, %66, %67}, %68, p, 1, 1, 1;\n}\n"
    : "+f"(d[0]), "+f"(d[1]), "+f"(d[2]), "+f"(d[3]), "+f"(d[4]), "+f"(d[5]), "+f"(d[6]), "+f"(d[7]),
      "+f"(d[8]), "+f"(d[9]), "+f"(d[10]), "+f"(d[11]), "+f"(d[12]), "+f"(d[13]), "+f"(d[14]), "+f"(d[15]),
      "+f"(d[16]), "+f"(d[17]), "+f"(d[18]), "+f"(d[19]), "+f"(d[20]), "+f"(d[21]), "+f"(d[22]), "+f"(d[23]),
      "+f"(d[24]), "+f"(d[25]), "+f"(d[26]), "+f"(d[27]), "+f"(d[28]), "+f"(d[29]), "+f"(d[30]), "+f"(d[31]),
      "+f"(d[32]), "+f"(d[33]), "+f"(d[34]), "+f"(d[35]), "+f"(d[36]), "+f"(d[37]), "+f"(d[38]), "+f"(d[39]),
      "+f"(d[40]), "+f"(d[41]), "+f"(d[42]), "+f"(d[43]), "+f"(d[44]), "+f"(d[45]), "+f"(d[46]), "+f"(d[47]),
      "+f"(d[48]), "+f"(d[49]), "+f"(d[50]), "+f"(d[51]), "+f"(d[52]), "+f"(d[53]), "+f"(d[54]), "+f"(d[55]),
      "+f"(d[56]), "+f"(d[57]), "+f"(d[58]), "+f"(d[59]), "+f"(d[60]), "+f"(d[61]), "+f"(d[62]), "+f"(d[63])
    : "r"(a0), "r"(a1), "r"(a2), "r"(a3), "l"(db), "r"(scale_d));
}
__device__ __forceinline__ void mma_rs(float (&d)[64], uint32_t a0, uint32_t a1, uint32_t a2, uint32_t a3, uint64_t db, int scale_d) {
  asm volatile("{\n.reg .pred p;\nsetp.ne.b32 p, %69, 0;\n"
    "wgmma.mma_async.sync.aligned.m64n128k16.f32.bf16.bf16 {"
    "%0, %1, %2, %3, %4, %5, %6, %7, %8, %9, %10, %11, %12, %13, %14, %15, "
    "%16, %17, %18, %19, %20, %21, %22, %23, %24, %25, %26, %27, %28, %29, %30, %31, "
    "%32, %33, %34, %35, %36, %37, %38, %39, %40, %41, %42, %43, %44, %45, %46, %47, "
    "%48, %49, %50, %51, %52, %53, %54, %55, %56, %57, %58, %59, %60, %61, %62, %63}, "
    "{%64, %65, %66, %67}, %68, p, 1, 1, 0;\n}\n"
    : "+f"(d[0]), "+f"(d[1]), "+f"(d[2]), "+f"(d[3]), "+f"(d[4]), "+f"(d[5]), "+f"(d[6]), "+f"(d[7]),
      "+f"(d[8]), "+f"(d[9]), "+f"(d[10]), "+f"(d[11]), "+f"(d[12]), "+f"(d[13]), "+f"(d[14]), "+f"(d[15]),
      "+f"(d[16]), "+f"(d[17]), "+f"(d[18]), "+f"(d[19]), "+f"(d[20]), "+f"(d[21]), "+f"(d[22]), "+f"(d[23]),
      "+f"(d[24]), "+f"(d[25]), "+f"(d[26]), "+f"(d[27]), "+f"(d[28]), "+f"(d[29]), "+f"(d[30]), "+f"(d[31]),
      "+f"(d[32]), "+f"(d[33]), "+f"(d[34]), "+f"(d[35]), "+f"(d[36]), "+f"(d[37]), "+f"(d[38]), "+f"(d[39]),
      "+f"(d[40]), "+f"(d[41]), "+f"(d[42]), "+f"(d[43]), "+f"(d[44]), "+f"(d[45]), "+f"(d[46]), "+f"(d[47]),
      "+f"(d[48]), "+f"(d[49]), "+f"(d[50]), "+f"(d[51]), "+f"(d[52]), "+f"(d[53]), "+f"(d[54]), "+f"(d[55]),
      "+f"(d[56]), "+f"(d[57]), "+f"(d[58]), "+f"(d[59]), "+f"(d[60]), "+f"(d[61]), "+f"(d[62]), "+f"(d[63])
    : "r"(a0), "r"(a1), "r"(a2), "r"(a3), "l"(db), "r"(scale_d));
}
__device__ __forceinline__ void mma_ss(float (&d)[64], uint64_t da, uint64_t db, int scale_d) {
  asm volatile("{\n.reg .pred p;\nsetp.ne.b32 p, %66, 0;\n"
    "wgmma.mma_async.sync.aligned.m64n128k16.f32.bf16.bf16 {"
    "%0, %1, %2, %3, %4, %5, %6, %7, %8, %9, %10, %11, %12, %13, %14, %15, "
    "%16, %17, %18, %19, %20, %21, %22, %23, %24, %25, %26, %27, %28, %29, %30, %31, "
    "%32, %33, %34, %35, %36, %37, %38, %39, %40, %41, %42, %43, %44, %45, %46, %47, "
    "%48, %49, %50, %51, %52, %53, %54, %55, %56, %57, %58, %59, %60, %61, %62, %63}, "
    "%64, %65, p, 1, 1, 0, 0;\n}\n"
    : "+f"(d[0]), "+f"(d[1]), "+f"(d[2]), "+f"(d[3]), "+f"(d[4]), "+f"(d[5]), "+f"(d[6]), "+f"(d[7]),
      "+f"(d[8]), "+f"(d[9]), "+f"(d[10]), "+f"(d[11]), "+f"(d[12]), "+f"(d[13]), "+f"(d[14]), "+f"(d[15]),
      "+f"(d[16]), "+f"(d[17]), "+f"(d[18]), "+f"(d[19]), "+f"(d[20]), "+f"(d[21]), "+f"(d[22]), "+f"(d[23]),
      "+f"(d[24]), "+f"(d[25]), "+f"(d[26]), "+f"(d[27]), "+f"(d[28]), "+f"(d[29]), "+f"(d[30]), "+f"(d[31]),
      "+f"(d[32]), "+f"(d[33]), "+f"(d[34]), "+f"(d[35]), "+f"(d[36]), "+f"(d[37]), "+f"(d[38]), "+f"(d[39]),
      "+f"(d[40]), "+f"(d[41]), "+f"(d[42]), "+f"(d[43]), "+f"(d[44]), "+f"(d[45]), "+f"(d[46]), "+f"(d[47]),
      "+f"(d[48]), "+f"(d[49]), "+f"(d[50]), "+f"(d[51]), "+f"(d[52]), "+f"(d[53]), "+f"(d[54]), "+f"(d[55]),
      "+f"(d[56]), "+f"(d[57]), "+f"(d[58]), "+f"(d[59]), "+f"(d[60]), "+f"(d[61]), "+f"(d[62]), "+f"(d[63])
    : "l"(da), "l"(db), "r"(scale_d));
}
__device__ __forceinline__ void mma_ss_ta(float (&d)[64], uint64_t da, uint64_t db, int scale_d) {
  asm volatile("{\n.reg .pred p;\nsetp.ne.b32 p, %66, 0;\n"
    "wgmma.mma_async.sync.aligned.m64n128k16.f32.bf16.bf16 {"
    "%0, %1, %2, %3, %4, %5, %6, %7, %8, %9, %10, %11, %12, %13, %14, %15, "
    "%16, %17, %18, %19, %20, %21, %22, %23, %24, %25, %26, %27, %28, %29, %30, %31, "
    "%32, %33, %34, %35, %36, %37, %38, %39, %40, %41, %42, %43, %44, %45, %46, %47, "
    "%48, %49, %50, %51, %52, %53, %54, %55, %56, %57, %58, %59, %60, %61, %62, %63}, "
    "%64, %65, p, 1, 1, 1, 0;\n}\n"
    : "+f"(d[0]), "+f"(d[1]), "+f"(d[2]), "+f"(d[3]), "+f"(d[4]), "+f"(d[5]), "+f"(d[6]), "+f"(d[7]),
      "+f"(d[8]), "+f"(d[9]), "+f"(d[10]), "+f"(d[11]), "+f"(d[12]), "+f"(d[13]), "+f"(d[14]), "+f"(d[15]),
      "+f"(d[16]), "+f"(d[17]), "+f"(d[18]), "+f"(d[19]), "+f"(d[20]), "+f"(d[21]), "+f"(d[22]), "+f"(d[23]),
      "+f"(d[24]), "+f"(d[25]), "+f"(d[26]), "+f"(d[27]), "+f"(d[28]), "+f"(d[29]), "+f"(d[30]), "+f"(d[31]),
      "+f"(d[32]), "+f"(d[33]), "+f"(d[34]), "+f"(d[35]), "+f"(d[36]), "+f"(d[37]), "+f"(d[38]), "+f"(d[39]),
      "+f"(d[40]), "+f"(d[41]), "+f"(d[42]), "+f"(d[43]), "+f"(d[44]), "+f"(d[45]), "+f"(d[46]), "+f"(d[47]),
      "+f"(d[48]), "+f"(d[49]), "+f"(d[50]), "+f"(d[51]), "+f"(d[52]), "+f"(d[53]), "+f"(d[54]), "+f"(d[55]),
      "+f"(d[56]), "+f"(d[57]), "+f"(d[58]), "+f"(d[59]), "+f"(d[60]), "+f"(d[61]), "+f"(d[62]), "+f"(d[63])
    : "l"(da), "l"(db), "r"(scale_d));
}

__device__ __forceinline__ void mbar_init(uint32_t bar, int cnt) { asm volatile("mbarrier.init.shared::cta.b64 [%0], %1;" :: "r"(bar), "r"(cnt) : "memory"); }
__device__ __forceinline__ void mbar_arrive(uint32_t bar) { asm volatile("mbarrier.arrive.shared::cta.b64 _, [%0];" :: "r"(bar) : "memory"); }
__device__ __forceinline__ void mbar_arrive_remote(uint32_t bar) { asm volatile("mbarrier.arrive.relaxed.cluster.shared::cluster.b64 _, [%0];" :: "r"(bar) : "memory"); }
__device__ __forceinline__ void mbar_expect_tx(uint32_t bar, uint32_t bytes) { asm volatile("mbarrier.arrive.expect_tx.shared::cta.b64 _, [%0], %1;" :: "r"(bar), "r"(bytes) : "memory"); }
__device__ __forceinline__ void mbar_wait(uint32_t bar, uint32_t parity) {
  uint32_t ok; int it = 0;
  do {
    asm volatile("{\n.reg .pred p;\nmbarrier.try_wait.parity.shared::cta.b64 p, [%1], %2;\nselp.u32 %0, 1, 0, p;\n}\n" : "=r"(ok) : "r"(bar), "r"(parity) : "memory");
  } while (!ok && ++it < SPIN);
}
__device__ __forceinline__ void mbar_wait_cluster(uint32_t bar, uint32_t parity) {
  uint32_t ok; int it = 0;
  do {
    asm volatile("{\n.reg .pred p;\nmbarrier.try_wait.parity.acquire.cluster.shared::cta.b64 p, [%1], %2;\nselp.u32 %0, 1, 0, p;\n}\n" : "=r"(ok) : "r"(bar), "r"(parity) : "memory");
  } while (!ok && ++it < SPIN);
}
__device__ __forceinline__ void bulk_g2s(uint32_t dst, const void* src, uint32_t bytes, uint32_t bar) {
  asm volatile("cp.async.bulk.shared::cluster.global.mbarrier::complete_tx::bytes [%0], [%1], %2, [%3];" :: "r"(dst), "l"(src), "r"(bytes), "r"(bar) : "memory");
}
__device__ __forceinline__ void cp16(uint32_t dst, const void* src) { asm volatile("cp.async.cg.shared.global [%0], [%1], 16;" :: "r"(dst), "l"(src) : "memory"); }
__device__ __forceinline__ void cp_commit() { asm volatile("cp.async.commit_group;" ::: "memory"); }
template <int K> __device__ __forceinline__ void cp_wait() { asm volatile("cp.async.wait_group %0;" :: "n"(K) : "memory"); }
__device__ __forceinline__ void fence_async_s() { asm volatile("fence.proxy.async.shared::cta;" ::: "memory"); }
__device__ __forceinline__ void fence_async_g() { asm volatile("fence.proxy.async.global;" ::: "memory"); }
__device__ __forceinline__ void bulk_s2g(void* dst, uint32_t src, uint32_t bytes) { asm volatile("cp.async.bulk.global.shared::cta.bulk_group [%0], [%1], %2;" :: "l"(dst), "r"(src), "r"(bytes) : "memory"); }
__device__ __forceinline__ void bulk_s2s(uint32_t dst, uint32_t src, uint32_t bytes, uint32_t bar) { asm volatile("cp.async.bulk.shared::cluster.shared::cta.mbarrier::complete_tx::bytes [%0], [%1], %2, [%3];" :: "r"(dst), "r"(src), "r"(bytes), "r"(bar) : "memory"); }
__device__ __forceinline__ void wg_fence() { asm volatile("wgmma.fence.sync.aligned;" ::: "memory"); }
__device__ __forceinline__ void wg_commit() { asm volatile("wgmma.commit_group.sync.aligned;" ::: "memory"); }
template <int K> __device__ __forceinline__ void wg_wait() { asm volatile("wgmma.wait_group.sync.aligned %0;" :: "n"(K) : "memory"); }
__device__ __forceinline__ void bar_sync(int id, int n) { asm volatile("bar.sync %0, %1;" :: "r"(id), "r"(n) : "memory"); }
__device__ __forceinline__ void bar_arrive(int id, int n) { asm volatile("bar.arrive %0, %1;" :: "r"(id), "r"(n) : "memory"); }
__device__ __forceinline__ float ex2(float x) { float y; asm("ex2.approx.ftz.f32 %0, %1;" : "=f"(y) : "f"(x)); return y; }
__device__ __forceinline__ float lg2(float x) { float y; asm("lg2.approx.f32 %0, %1;" : "=f"(y) : "f"(x)); return y; }
__device__ __forceinline__ uint32_t pack_bf16(float lo, float hi) { uint32_t r; asm("cvt.rn.bf16x2.f32 %0, %1, %2;" : "=r"(r) : "f"(hi), "f"(lo)); return r; }
__device__ __forceinline__ uint32_t pack_f16(float lo, float hi) { uint32_t r; asm("cvt.rn.f16x2.f32 %0, %1, %2;" : "=r"(r) : "f"(hi), "f"(lo)); return r; }
__device__ __forceinline__ uint32_t pack_f16_sat(float lo, float hi) { uint32_t r; asm("cvt.rn.satfinite.f16x2.f32 %0, %1, %2;" : "=r"(r) : "f"(hi), "f"(lo)); return r; }
__device__ __forceinline__ float bf_lo(uint32_t u) { return __uint_as_float(u << 16); }
__device__ __forceinline__ float bf_hi(uint32_t u) { return __uint_as_float(u & 0xffff0000u); }
__device__ __forceinline__ float h_lo(uint32_t u) { return __half2float(__ushort_as_half((unsigned short)(u & 0xffffu))); }
__device__ __forceinline__ float h_hi(uint32_t u) { return __half2float(__ushort_as_half((unsigned short)(u >> 16))); }
__device__ __forceinline__ float quad_sum(float v) { v += __shfl_xor_sync(~0u, v, 1); return v + __shfl_xor_sync(~0u, v, 2); }
__device__ __forceinline__ float quad_max(float v) { v = fmaxf(v, __shfl_xor_sync(~0u, v, 1)); return fmaxf(v, __shfl_xor_sync(~0u, v, 2)); }
template <int K> __device__ __forceinline__ void pin(float (&d)[K]) {
#pragma unroll
  for (int i = 0; i < K; i++) asm volatile("" : "+f"(d[i]) :: "memory");
}
template <int K> __device__ __forceinline__ void pin(uint32_t (&d)[K]) {
#pragma unroll
  for (int i = 0; i < K; i++) asm volatile("" : "+r"(d[i]) :: "memory");
}
__device__ __forceinline__ uint64_t desc_k(uint32_t a) { return (uint64_t)((a & 0x3FFFF) >> 4) | (1ull << 16) | (128ull << 32) | (1ull << 62); }
__device__ __forceinline__ uint64_t desc_mn(uint32_t a) { return (uint64_t)((a & 0x3FFFF) >> 4) | (64ull << 16) | (128ull << 32) | (1ull << 62); }
__device__ __forceinline__ constexpr uint32_t koff(int ks) { return ((ks >> 2) * 1024 + (ks & 3) * 32) >> 4; }
__device__ __forceinline__ uint32_t tile_off(int row, int chunk) { return (row >> 3) * 2048 + (chunk >> 3) * 1024 + (row & 7) * 128 + (((chunk & 7) ^ (row & 7)) << 4); }
__device__ __forceinline__ unsigned ld_acq(const unsigned* p) { unsigned v; asm volatile("ld.acquire.gpu.global.u32 %0, [%1];" : "=r"(v) : "l"(p) : "memory"); return v; }
__device__ __forceinline__ void st_rel(unsigned* p, unsigned v) { asm volatile("st.release.gpu.global.u32 [%0], %1;" :: "l"(p), "r"(v) : "memory"); }
__device__ __forceinline__ void wait_flag(const unsigned* p, unsigned tag) {
#pragma unroll 1
  for (int it = 0; it < SPIN && ld_acq(p) != tag; it++) {}
}
__device__ __forceinline__ uint32_t mapa(uint32_t a, uint32_t rank) { uint32_t r; asm("mapa.shared::cluster.u32 %0, %1, %2;" : "=r"(r) : "r"(a), "r"(rank)); return r; }
__device__ __forceinline__ void st_async4(uint32_t a, uint32_t x, uint32_t y, uint32_t z, uint32_t w, uint32_t bar) { asm volatile("st.async.weak.shared::cluster.mbarrier::complete_tx::bytes.v4.b32 [%0], {%1, %2, %3, %4}, [%5];" :: "r"(a), "r"(x), "r"(y), "r"(z), "r"(w), "r"(bar) : "memory"); }
__device__ __forceinline__ void st_async2(uint32_t a, float x, float y, uint32_t bar) { asm volatile("st.async.weak.shared::cluster.mbarrier::complete_tx::bytes.v2.f32 [%0], {%1, %2}, [%3];" :: "r"(a), "f"(x), "f"(y), "r"(bar) : "memory"); }
__device__ __forceinline__ void sts4(uint32_t a, uint4 v) { asm volatile("st.shared.v4.b32 [%0], {%1, %2, %3, %4};" :: "r"(a), "r"(v.x), "r"(v.y), "r"(v.z), "r"(v.w) : "memory"); }
__device__ __forceinline__ uint32_t hadd2(uint32_t a, uint32_t b) { uint32_t r; asm("add.rn.f16x2 %0, %1, %2;" : "=r"(r) : "r"(a), "r"(b)); return r; }
__device__ __forceinline__ uint32_t hmix2(uint32_t a, uint32_t b, uint32_t f) { uint32_t r; asm("{\n.reg .b32 d;\nsub.rn.f16x2 d, %2, %1;\nfma.rn.f16x2 %0, d, %3, %1;\n}" : "=r"(r) : "r"(a), "r"(b), "r"(f)); return r; }
__device__ __forceinline__ uint4 lds4(uint32_t a) { uint4 v; asm volatile("ld.shared.v4.b32 {%0, %1, %2, %3}, [%4];" : "=r"(v.x), "=r"(v.y), "=r"(v.z), "=r"(v.w) : "r"(a) : "memory"); return v; }
__device__ __forceinline__ float2 lds2(uint32_t a) { float2 v; asm volatile("ld.shared.v2.f32 {%0, %1}, [%2];" : "=f"(v.x), "=f"(v.y) : "r"(a) : "memory"); return v; }

template <bool PERM> __device__ __forceinline__ void stage_w(uint32_t dst, const __nv_bfloat16* w, int t) {
  const int r = t >> 4, c = t & 15;
#pragma unroll
  for (int i = 0; i < 16; i++) {
    const int lr = PERM ? ((i >> 2) * 32 + (r >> 2) * 16 + ((r >> 1) & 1) * 8 + (i & 3) * 2 + (r & 1)) : i * 8 + r;
    cp16(dst + tile_off(lr, c), w + (i * 128 + t) * 8);
  }
}

__global__ void __launch_bounds__(384, 1) __cluster_dims__(2, 1, 1)
graphgps_kernel(const __nv_bfloat16* __restrict__ x, const int* __restrict__ esrc, const int* __restrict__ edst,
                const __nv_bfloat16* __restrict__ deg_inv, const __nv_bfloat16* __restrict__ wmsg,
                const __nv_bfloat16* __restrict__ wq, const __nv_bfloat16* __restrict__ wk,
                const __nv_bfloat16* __restrict__ wv, const __nv_bfloat16* __restrict__ wout,
                __nv_bfloat16* __restrict__ out) {
  extern __shared__ uint8_t smem_raw[];
  const uint32_t sb = ((uint32_t)__cvta_generic_to_shared(smem_raw) + 1023) & ~1023u;
  const uint32_t bars = sb + SM_BAR;
  const int tid = threadIdx.x, lane = tid & 31;
  const int wg = __shfl_sync(~0u, tid >> 7, 0);
  const int cl = blockIdx.x >> 1, rank = blockIdx.x & 1;
  const bool isY = cl >= 52 && cl < 65, isZ = cl == 65, isX1 = cl < 52 && rank == 1, isX0 = cl < 52 && rank == 0;
  const int grp = isY ? (cl - 52) * 2 + rank : cl >> 1;
  const int qfin = isZ ? 78 : isY ? 3 * grp + 1 : 3 * grp + (cl & 1) * 2;
  const int ntiles = isZ ? 35 : 42;
  const int jsw = isX1 ? 14 : 0;
  const bool writes_h = !isX1 && !(isZ && rank == 1);
  PROBE(wg == 2 ? 0 : 31);

  if (wg == 2) {
    asm volatile("setmaxnreg.dec.sync.aligned.u32 40;");
    const int t = tid - 256, pw = __shfl_sync(~0u, t >> 5, 0);
    stage_w<true>(sb + SM_KV + 2 * TILE_B, wq, t); cp_commit();
    unsigned long long tk = 0;
    if (t == 32) tk = atomicAdd(&g_ticket, 1ull);
    if (t < B_TAG) {
      const int cnt = t < B_EMPTY ? 1 : t < B_WQ ? 2 : t <= B_WZ ? 128 : t == B_WFREE ? 2 : t == B_G ? 96 : (t == B_M && isY) ? 96 : 1;
      mbar_init(bars + 8 * t, cnt);
      if (t == B_M && !isY) mbar_expect_tx(bars + 8 * t, PART_B);
      if (t == B_Q2 && isX1) mbar_expect_tx(bars + 8 * t, 2 * PART_B);
      if (t == B_FULL && isX1) mbar_expect_tx(bars + 8 * t, 32768);
      asm volatile("fence.mbarrier_init.release.cluster;" ::: "memory");
    }
    stage_w<false>(sb + SM_KV + 3 * TILE_B, wk, t); cp_commit();
    bar_sync(0, 384);
    asm volatile("barrier.cluster.arrive.relaxed.aligned;" ::: "memory");
    if (isZ) { stage_w<false>(sb + SM_G, wout, t); stage_w<false>(sb + SM_M, rank ? wv : wmsg, t); }
    cp_commit();
    sts4(sb + SM_KV + 32768 + t * 16, make_uint4(0, 0, 0, 0)); sts4(sb + SM_KV + 32768 + 2048 + t * 16, make_uint4(0, 0, 0, 0));
    cp_wait<2>(); fence_async_s(); mbar_arrive(bars + 8 * B_WQ);
    PROBE(29);
    cp_wait<1>(); fence_async_s(); mbar_arrive(bars + 8 * B_WK);
    if (t == 32) asm volatile("st.shared.u64 [%0], %1;" :: "r"(bars + 8 * B_TAG), "l"(tk / NCTA + 1) : "memory");
    cp_wait<0>(); fence_async_s(); mbar_arrive(bars + 8 * B_WZ);
    asm volatile("barrier.cluster.wait.aligned;" ::: "memory");
    bar_sync(5, 128);
    PROBE(30);
    unsigned long long epoch; asm volatile("ld.shared.u64 %0, [%1];" : "=l"(epoch) : "r"(bars + 8 * B_TAG) : "memory");
    const unsigned tag = (unsigned)epoch;
    if (pw == 0) {
      if (isX1 && lane == 0) { mbar_wait_cluster(bars + 8 * B_FULL, 0); mbar_arrive_remote(mapa(bars + 8 * B_S0, 0)); }
#pragma unroll 1
      for (int i = lane; i < 79; i += 32) wait_flag(&g_hflag[i], tag);
      __syncwarp();
      PROBE1(19);
      if (lane == 0) {
        fence_async_g();
        const int qB = 3 * grp + 1;
        int row, wrap;
        if (isZ) { mbar_expect_tx(bars + 8 * B_FULL, 32768); bulk_g2s(sb + SM_KV, g_h + rank * 32768, 32768, bars + 8 * B_FULL); row = 256 + rank * 34 * T; wrap = 10048; }
        else if (isX0) { row = (qfin + 1) * 128; wrap = 10064; }
        else { row = (qB + 2) * 128 + (isY ? 26 : (cl & 1) * 13) * T; wrap = 10032; }
        int st = 1, ph = 1;
#pragma unroll 1
        for (int j = 1; j < ntiles + 2; j++) {
          if (j == jsw) { row = (qfin + 1) * 128 + 41 * T; wrap = 10064; }
          if (row >= wrap) row -= wrap;
          if (j == 2) mbar_wait(bars + 8 * B_WFREE, 0);
          if (j == NST && isX0) mbar_wait_cluster(bars + 8 * B_S0, 0);
          if (j == ntiles) { for (int i = 0; i < 4; i++) wait_flag(&g_wflag[i], tag); fence_async_g(); }
          mbar_wait(bars + 8 * (B_EMPTY + st), ph);
          const uint32_t dst = sb + SM_KV + st * TILE_B, fb = bars + 8 * (B_FULL + st);
          if (j < ntiles) {
            mbar_expect_tx(fb, TILE_B);
            const int n1 = min(T, wrap - row);
            bulk_g2s(dst, g_h + row * 256, n1 * 256, fb);
            if (n1 < T) bulk_g2s(dst + n1 * 256, g_h, (T - n1) * 256, fb);
            row += T;
          } else {
            mbar_expect_tx(fb, 32768);
            bulk_g2s(dst, g_wc + (j - ntiles) * 32768, 32768, fb);
          }
          if (j == 1) PROBE1(1);
          if (++st == NST) { st = 0; ph ^= 1; }
        }
      }
    } else {
      const int gt = t - 32, gw = pw - 1;
      if (writes_h && gw == 0) {
        bar_sync(3, 288);
        if (lane == 0) {
          if (isX0) bulk_s2s(mapa(sb + SM_KV, 1), sb + SM_KV, 32768, mapa(bars + 8 * B_FULL, 1));
          if (!isZ) mbar_arrive(bars + 8 * B_FULL);
          bulk_s2g(g_h + qfin * 32768, sb + SM_KV, 32768);
          asm volatile("cp.async.bulk.commit_group;\ncp.async.bulk.wait_group 0;" ::: "memory");
          PROBE1(20);
          st_rel(&g_hflag[qfin], tag);
          PROBE1(21);
        }
        __syncwarp();
      }
      {
        int e4 = blockIdx.x * 96 + gt;
        int4 s4 = __ldg((const int4*)esrc + e4), d4 = __ldg((const int4*)edst + e4);
#pragma unroll 1
        for (; e4 < EE / 4; e4 += NCTA * 96) {
          const int s[4] = {s4.x, s4.y, s4.z, s4.w}, d[4] = {d4.x, d4.y, d4.z, d4.w};
          int slot[4];
#pragma unroll
          for (int k = 0; k < 4; k++) slot[k] = atomicAdd(&g_cnt[d[k]], 1);
          if (e4 + NCTA * 96 < EE / 4) { s4 = __ldg((const int4*)esrc + e4 + NCTA * 96); d4 = __ldg((const int4*)edst + e4 + NCTA * 96); }
#pragma unroll
          for (int k = 0; k < 4; k++) {
            if (slot[k] < CAP) g_ell[d[k] * CAP + slot[k]] = s[k] + 1;
            else g_ovf_next[e4 * 4 + k] = atomicExch(&g_ovf_head[d[k]], e4 * 4 + k);
          }
        }
      }
      if (isZ && gw < 2) {
        bar_sync(6 + gw, 160);
        if (lane == 0) st_rel(&g_wflag[rank * 2 + gw], tag);
      }
      if (writes_h) bar_sync(4, 352); else bar_sync(5, 96);
      if (gt == 0) {
        asm volatile("red.release.gpu.global.add.u64 [%0], 1;" :: "l"(&g_ellctr) : "memory");
#pragma unroll 1
        for (int it = 0; it < SPIN; it++) {
          unsigned long long v; asm volatile("ld.acquire.gpu.global.u64 %0, [%1];" : "=l"(v) : "l"(&g_ellctr) : "memory");
          if (v >= epoch * NCTA) break;
          __nanosleep(100);
        }
      }
      bar_sync(5, 96);
      if (gw == 0) PROBE1(2);
      const int lr0 = isY ? 0 : 64;
      const int row0 = qfin * 128 + (isY ? 0 : rank * 64) - lr0;
      const uint8_t* hp = g_hp + (lane & 15) * 16;
#pragma unroll 1
      for (int lr = lr0 + gw * 2 + (lane >> 4); lr < 128; lr += 6) {
        const int row = row0 + lr;
        uint4* ell = (uint4*)(g_ell + row * CAP);
        const int n = __ldcg(&g_cnt[row]);
        uint4 id = __ldcg(ell);
        const float di = row < NN ? __bfloat162float(deg_inv[row]) : 0.f;
        const int nb = (min(max(n, __shfl_xor_sync(~0u, n, 16)), CAP) + 3) >> 2;
        uint4 a = make_uint4(0, 0, 0, 0);
#pragma unroll 1
        for (int b = 0; b < nb; b++) {
          const uint4 v0 = __ldcg((const uint4*)(hp + (size_t)id.x * 256)), v1 = __ldcg((const uint4*)(hp + (size_t)id.y * 256));
          const uint4 v2 = __ldcg((const uint4*)(hp + (size_t)id.z * 256)), v3 = __ldcg((const uint4*)(hp + (size_t)id.w * 256));
          id = __ldcg(ell + ((b + 1) & 7));
          a.x = hadd2(a.x, hadd2(hadd2(v0.x, v1.x), hadd2(v2.x, v3.x)));
          a.y = hadd2(a.y, hadd2(hadd2(v0.y, v1.y), hadd2(v2.y, v3.y)));
          a.z = hadd2(a.z, hadd2(hadd2(v0.z, v1.z), hadd2(v2.z, v3.z)));
          a.w = hadd2(a.w, hadd2(hadd2(v0.w, v1.w), hadd2(v2.w, v3.w)));
        }
        float f[8] = {h_lo(a.x), h_hi(a.x), h_lo(a.y), h_hi(a.y), h_lo(a.z), h_hi(a.z), h_lo(a.w), h_hi(a.w)};
        if (n > CAP) {
          int e = __ldcg(&g_ovf_head[row]);
#pragma unroll 1
          for (int k = CAP; k < n; k++) {
            const uint4 v = __ldcg((const uint4*)(hp + (size_t)(__ldg(esrc + e) + 1) * 256));
            f[0] += h_lo(v.x); f[1] += h_hi(v.x); f[2] += h_lo(v.y); f[3] += h_hi(v.y);
            f[4] += h_lo(v.z); f[5] += h_hi(v.z); f[6] += h_lo(v.w); f[7] += h_hi(v.w);
            e = __ldcg(&g_ovf_next[e]);
          }
        }
        __syncwarp();
        if ((lane & 15) < 8) ell[lane & 15] = make_uint4(0, 0, 0, 0);
        if ((lane & 15) == 8) g_cnt[row] = 0;
        sts4(sb + SM_G + tile_off(lr, lane & 15), make_uint4(pack_bf16(f[0] * di, f[1] * di), pack_bf16(f[2] * di, f[3] * di), pack_bf16(f[4] * di, f[5] * di), pack_bf16(f[6] * di, f[7] * di)));
      }
      fence_async_s();
      mbar_arrive(bars + 8 * B_G);
      if (gw == 0) PROBE1(3);
      if (isX1 && gw < 2) {
        bar_sync(6 + gw, 160);
        if (lane == 0) st_rel(&g_pflag[grp * 4 + (cl & 1) * 2 + gw], tag);
      }
      if (isY) {
        if (lane < 4) wait_flag(&g_pflag[grp * 4 + lane], tag);
        __syncwarp();
#pragma unroll 1
        for (int u = gt; u < 256; u += 96) {
          const int w = u >> 7, tt = u & 127;
          const uint8_t* pa = g_part + (grp * 4 + w) * PART_B;
          const uint8_t* pb = pa + 2 * PART_B;
          const float2 la = __ldcg((const float2*)(pa + 16384) + tt), lb = __ldcg((const float2*)(pb + 16384) + tt);
          const float x0 = fmaxf(la.x, lb.x), x1 = fmaxf(la.y, lb.y);
          const float wb0 = ex2(lb.x - x0), wb1 = ex2(lb.y - x1);
          const float s0 = ex2(la.x - x0) + wb0, s1 = ex2(la.y - x1) + wb1;
          const uint32_t f0 = pack_f16(__fdividef(wb0, s0), __fdividef(wb0, s0)), f1 = pack_f16(__fdividef(wb1, s1), __fdividef(wb1, s1));
          asm volatile("st.shared.v2.f32 [%0], {%1, %2};" :: "r"(sb + SM_LAM + u * 8), "f"(x0 + lg2(s0)), "f"(x1 + lg2(s1)) : "memory");
#pragma unroll 2
          for (int k = 0; k < 8; k++) {
            const uint4 a = __ldcg((const uint4*)(pa + k * 2048) + tt), b = __ldcg((const uint4*)(pb + k * 2048) + tt);
            sts4(sb + SM_M + w * 16384 + k * 2048 + tt * 16, make_uint4(hmix2(a.x, b.x, f0), hmix2(a.y, b.y, f1), hmix2(a.z, b.z, f0), hmix2(a.w, b.w, f1)));
          }
        }
        mbar_arrive(bars + 8 * B_M);
        if (gw == 0) PROBE1(4);
      }
    }
  } else {
    const int t = tid & 127, q = lane & 3, rr = lane >> 2;
    const int blk_fin = isY ? wg : wg ^ 1 ^ rank;
    float O[64], S[T / 2];
    uint32_t P[T / 4], Q[32];
    {
      const int lr0 = (isX1 ? wg : blk_fin) * 64 + (t >> 5) * 16 + rr;
      const int r0 = (isX1 ? 3 * grp + 1 : qfin) * 128 + lr0;
      uint4 xv[8];
#pragma unroll
      for (int i = 0; i < 8; i++) {
        const int r = r0 + (i >> 2) * 8;
        xv[i] = r < NN ? __ldg((const uint4*)x + r * 16 + (i & 3) * 4 + q) : make_uint4(0, 0, 0, 0);
      }
      PROBE(24);
      asm volatile("setmaxnreg.inc.sync.aligned.u32 232;");
      bar_sync(0, 384);
      asm volatile("barrier.cluster.arrive.relaxed.aligned;" ::: "memory");
      PROBE(25);
      float v[64];
#pragma unroll
      for (int h = 0; h < 2; h++) {
#pragma unroll
        for (int i = 0; i < 4; i++) {
          const uint4 u = xv[h * 4 + i];
          float* w = v + 32 * h + 8 * i;
          w[0] = bf_lo(u.x); w[1] = bf_hi(u.x); w[2] = bf_lo(u.y); w[3] = bf_hi(u.y);
          w[4] = bf_lo(u.z); w[5] = bf_hi(u.z); w[6] = bf_lo(u.w); w[7] = bf_hi(u.w);
        }
        float s0 = 0.f, s1 = 0.f, s2 = 0.f, s3 = 0.f;
#pragma unroll
        for (int i = 0; i < 8; i++) { s0 += v[32 * h + 4 * i]; s1 += v[32 * h + 4 * i + 1]; s2 += v[32 * h + 4 * i + 2]; s3 += v[32 * h + 4 * i + 3]; }
        const float mean = quad_sum((s0 + s1) + (s2 + s3)) * (1.f / 128.f);
#pragma unroll
        for (int i = 0; i < 32; i++) v[32 * h + i] -= mean;
#pragma unroll
        for (int ks = 0; ks < 8; ks++) {
          Q[4 * ks + h] = pack_bf16(v[32 * h + 4 * ks], v[32 * h + 4 * ks + 1]);
          Q[4 * ks + 2 + h] = pack_bf16(v[32 * h + 4 * ks + 2], v[32 * h + 4 * ks + 3]);
        }
      }
      PROBE(27);
      mbar_wait(bars + 8 * B_WQ, 0);
      pin(Q); wg_fence();
#pragma unroll
      for (int ks = 0; ks < 8; ks++) mma_rs_t(O, Q[4 * ks], Q[4 * ks + 1], Q[4 * ks + 2], Q[4 * ks + 3], desc_mn(sb + SM_KV + 2 * TILE_B) + ks * 256, ks > 0);
      wg_commit();
      float rstd[2];
#pragma unroll
      for (int h = 0; h < 2; h++) {
        float s0 = 0.f, s1 = 0.f, s2 = 0.f, s3 = 0.f;
#pragma unroll
        for (int i = 0; i < 8; i++) {
          const float* w = v + 32 * h + 4 * i;
          s0 = fmaf(w[0], w[0], s0); s1 = fmaf(w[1], w[1], s1); s2 = fmaf(w[2], w[2], s2); s3 = fmaf(w[3], w[3], s3);
        }
        rstd[h] = rsqrtf(quad_sum((s0 + s1) + (s2 + s3)) * (1.f / 128.f) + 1e-5f);
      }
      if (writes_h) {
#pragma unroll
        for (int h = 0; h < 2; h++) {
          const float cc = r0 + h * 8 < NN ? COFF : 0.f, rs = rstd[h];
          const float off = fmaf(__shfl_sync(~0u, v[32 * h + 31], lane | 3) * rs, RS1, cc);
#pragma unroll
          for (int i = 0; i < 4; i++) {
            const float* w = v + 32 * h + 8 * i;
            sts4(sb + SM_KV + tile_off(lr0 + h * 8, 4 * i + q),
                 make_uint4(pack_f16(fmaf(w[0], rs, off), fmaf(w[1], rs, off)), pack_f16(fmaf(w[2], rs, off), fmaf(w[3], rs, off)),
                            pack_f16(fmaf(w[4], rs, off), fmaf(w[5], rs, off)), pack_f16(fmaf(w[6], rs, off), (i == 3 && q == 3) ? cc : fmaf(w[7], rs, off))));
          }
        }
        fence_async_s();
        bar_arrive(3, 288);
      }
      PROBE(5 + wg);
      wg_wait<0>(); pin(O); pin(Q);
#pragma unroll
      for (int i = 0; i < 32; i++) Q[i] = pack_bf16(O[2 * i], O[2 * i + 1]);
      mbar_wait(bars + 8 * B_WK, 0);
      pin(Q); wg_fence();
#pragma unroll
      for (int ks = 0; ks < 8; ks++) mma_rs(O, Q[4 * ks], Q[4 * ks + 1], Q[4 * ks + 2], Q[4 * ks + 3], desc_k(sb + SM_KV + 3 * TILE_B) + koff(ks), ks > 0);
      wg_commit();
      if (writes_h) {
#pragma unroll
        for (int i = 0; i < 8; i++) {
          const float* w = v + 8 * i; const float rs = rstd[i >> 2];
          *(uint4*)(g_hp + (r0 + (i >> 2) * 8 + 1) * 256 + ((i & 3) * 4 + q) * 16) =
              make_uint4(pack_f16(w[0] * rs, w[1] * rs), pack_f16(w[2] * rs, w[3] * rs), pack_f16(w[4] * rs, w[5] * rs), pack_f16(w[6] * rs, w[7] * rs));
        }
        bar_arrive(4, 352);
      }
      wg_wait<0>(); pin(O); pin(Q);
      if (t == 0) mbar_arrive(bars + 8 * B_WFREE);
      auto rot_adj = [&](int h) {
        float s0 = 0.f, s1 = 0.f;
#pragma unroll
        for (int i = 0; i < 16; i++) { s0 += O[4 * i + 2 * h]; s1 += O[4 * i + 2 * h + 1]; }
        return (quad_sum(s0 + s1) * RSN - __shfl_sync(~0u, O[61 + 2 * h], lane | 3)) * RS1;
      };
      {
        const float k0 = rstd[0] * QSCALE, k1 = rstd[1] * QSCALE;
        const float j0 = -rot_adj(0) * k0, j1 = -rot_adj(1) * k1;
#pragma unroll
        for (int i = 0; i < 16; i++) {
          Q[2 * i] = pack_f16_sat(fmaf(O[4 * i], k0, j0), fmaf(O[4 * i + 1], k0, j0));
          Q[2 * i + 1] = pack_f16_sat(fmaf(O[4 * i + 2], k1, j1), fmaf(O[4 * i + 3], k1, j1));
        }
        if (q == 3) { Q[30] &= 0xffffu; Q[31] &= 0xffffu; }
      }
      if (isZ) {
        mbar_wait(bars + 8 * B_WZ, 0);
        wg_fence();
#pragma unroll
        for (int ks = 0; ks < 8; ks++) mma_ss_ta(O, desc_mn(sb + SM_G + wg * 1024) + ks * 256, desc_k(sb + SM_M) + koff(ks), ks > 0);
        wg_commit(); wg_wait<0>(); pin(O);
        const float j0 = rank ? rot_adj(0) : 0.f, j1 = rank ? rot_adj(1) : 0.f;
#pragma unroll
        for (int h = 0; h < 2; h++) {
          const int e = wg * 64 + (t >> 5) * 16 + rr + h * 8;
          const int n = 8 * (4 * (e >> 5) + ((e >> 1) & 3)) + 2 * ((e >> 3) & 3) + (e & 1);
          const float j = h ? j1 : j0;
#pragma unroll
          for (int i = 0; i < 16; i++) {
            uint32_t u = pack_bf16(O[4 * i + 2 * h] - j, O[4 * i + 2 * h + 1] - j);
            if (i == 15 && q == 3 && rank) u &= 0xffffu;
            *(uint32_t*)(g_wc + rank * 32768 + tile_off(n, i) + q * 4) = u;
          }
        }
        bar_arrive(6 + wg, 160);
      }
      asm volatile("barrier.cluster.wait.aligned;" ::: "memory");
    }
    PROBE(7 + wg);

    float m0 = -3e38f, m1 = -3e38f;
    bool sticky = false;
    int accz = 0;
    auto issue_qk = [&](int st) {
      const uint64_t d = desc_k(sb + SM_KV + st * TILE_B);
#pragma unroll
      for (int ks = 0; ks < 8; ks++) mma_qk(S, Q[4 * ks], Q[4 * ks + 1], Q[4 * ks + 2], Q[4 * ks + 3], d + koff(ks), ks > 0);
    };
    auto issue_pv = [&](int st) {
      const uint64_t d = desc_mn(sb + SM_KV + st * TILE_B);
#pragma unroll
      for (int ks = 0; ks < T / 16; ks++) mma_pv(O, P[4 * ks], P[4 * ks + 1], P[4 * ks + 2], P[4 * ks + 3], d + ks * 256, ks > 0 ? 1 : accz);
    };
    auto exact = [&]() {
      const float q0 = h_hi(__shfl_sync(~0u, Q[30], lane | 3)), q1 = h_hi(__shfl_sync(~0u, Q[31], lane | 3));
      float x0 = fmaf(COFF, q0, m0), x1 = fmaf(COFF, q1, m1);
#pragma unroll
      for (int i = 0; i < T / 8; i++) { x0 = fmaxf(x0, fmaxf(S[4 * i], S[4 * i + 1])); x1 = fmaxf(x1, fmaxf(S[4 * i + 2], S[4 * i + 3])); }
      x0 = quad_max(x0); x1 = quad_max(x1);
      const __half n0 = __float2half_ru(fminf(fmaxf(fmaf(x0, -1.f / COFF, q0), -65504.f), 65504.f));
      const __half n1 = __float2half_ru(fminf(fmaxf(fmaf(x1, -1.f / COFF, q1), -65504.f), 65504.f));
      const float d0e = COFF * (q0 - __half2float(n0)), d1e = COFF * (q1 - __half2float(n1));
      const bool k0 = fabsf(x0 - d0e) > 1.f, k1 = fabsf(x1 - d1e) > 1.f;
      const float d0 = k0 ? x0 : d0e, d1 = k1 ? x1 : d1e;
      const float r0 = k0 ? fmaf(-COFF, q0, x0) : -COFF * __half2float(n0), r1 = k1 ? fmaf(-COFF, q1, x1) : -COFF * __half2float(n1);
      sticky = __any_sync(~0u, k0 || k1);
      if (accz) {
        const float a0 = ex2(m0 - r0), a1 = ex2(m1 - r1);
#pragma unroll
        for (int i = 0; i < 16; i++) { O[4 * i] *= a0; O[4 * i + 1] *= a0; O[4 * i + 2] *= a1; O[4 * i + 3] *= a1; }
      }
      m0 = r0; m1 = r1;
      if (q == 3) { Q[30] = (Q[30] & 0xffffu) | ((uint32_t)__half_as_ushort(n0) << 16); Q[31] = (Q[31] & 0xffffu) | ((uint32_t)__half_as_ushort(n1) << 16); }
#pragma unroll
      for (int i = 0; i < T / 8; i++) {
        P[2 * i] = pack_f16(ex2(S[4 * i] - d0), ex2(S[4 * i + 1] - d0));
        P[2 * i + 1] = pack_f16(ex2(S[4 * i + 2] - d1), ex2(S[4 * i + 3] - d1));
      }
    };
    auto fast = [&]() -> bool {
      uint32_t acc = 0;
#pragma unroll
      for (int i = 0; i < T / 8; i++) {
        P[2 * i] = pack_f16(ex2(S[4 * i]), ex2(S[4 * i + 1]));
        P[2 * i + 1] = pack_f16(ex2(S[4 * i + 2]), ex2(S[4 * i + 3]));
        asm("fma.rn.f16x2 %0, %1, %2, %0;" : "+r"(acc) : "r"(P[2 * i]), "r"(P[2 * i + 1]));
      }
      return __any_sync(~0u, (((acc & 0x7c007c00u) + 0x04000400u) & 0x80008000u) != 0);
    };
    float L0, L1;
    auto getL = [&]() { L0 = __shfl_sync(~0u, O[61], lane | 3); L1 = __shfl_sync(~0u, O[63], lane | 3); };
    auto norm_chunk = [&](int k, float i0, float c0, float i1, float c1) {
      return make_uint4(pack_f16(fmaf(O[8 * k], i0, c0), fmaf(O[8 * k + 1], i0, c0)), pack_f16(fmaf(O[8 * k + 2], i1, c1), fmaf(O[8 * k + 3], i1, c1)),
                        pack_f16(fmaf(O[8 * k + 4], i0, c0), fmaf(O[8 * k + 5], i0, c0)), pack_f16(fmaf(O[8 * k + 6], i1, c1), fmaf(O[8 * k + 7], i1, c1)));
    };

    if (wg == 1) bar_arrive(1, 256);
    int st = 0, ph = 0;
    mbar_wait_cluster(bars + 8 * B_FULL, 0);
    PROBE(9 + wg);
    bar_sync(1 + wg, 256);
    pin(Q); wg_fence();
#pragma unroll
    for (int ks = 0; ks < 8; ks++) mma_qk0(O, Q[4 * ks], Q[4 * ks + 1], Q[4 * ks + 2], Q[4 * ks + 3], desc_k(sb + SM_KV) + koff(ks), ks > 0);
    wg_commit();
    bar_arrive(2 - wg, 256);
    wg_wait<0>(); pin(O); pin(Q);
#pragma unroll
    for (int i = 0; i < T / 2; i++) S[i] = i < 64 ? O[i] : -3e38f;
    exact();
    if (isX0) {
      const uint32_t dq = mapa(sb + (wg ? SM_G : SM_M) + t * 16, 1), db = mapa(bars + 8 * B_Q2, 1);
#pragma unroll
      for (int k = 0; k < 8; k++) st_async4(dq + k * 2048, Q[4 * k], Q[4 * k + 1], Q[4 * k + 2], Q[4 * k + 3], db);
      st_async2(mapa(sb + SM_M2 + (wg ^ 1) * 1024 + t * 8, 1), m0, m1, db);
    }
    PROBE(22 + wg);
    for (int j = 1; j < ntiles; j++) {
      const int pst = st;
      if (++st == NST) { st = 0; ph ^= 1; }
      if (j == jsw) {
        mbar_wait_cluster(bars + 8 * B_Q2, 0);
#pragma unroll
        for (int k = 0; k < 8; k++) { const uint4 v = lds4(sb + (wg ? SM_M : SM_G) + k * 2048 + t * 16); Q[4 * k] = v.x; Q[4 * k + 1] = v.y; Q[4 * k + 2] = v.z; Q[4 * k + 3] = v.w; }
      }
      bar_sync(1 + wg, 256);
      pin(S); pin(O); pin(P); pin(Q); wg_fence();
      issue_pv(pst);
      mbar_wait(bars + 8 * (B_FULL + st), ph);
      issue_qk(st);
      wg_commit();
      bar_arrive(2 - wg, 256);
      wg_wait<0>(); pin(S); pin(O); pin(P); pin(Q);
      if (t == 0) mbar_arrive(bars + 8 * (B_EMPTY + pst));
      accz = 1;
      if (j == jsw) {
        getL();
        uint8_t* dst = g_part + (grp * 4 + (cl & 1) * 2 + wg) * PART_B;
        const float i0 = COFF / L0, i1 = COFF / L1;
#pragma unroll
        for (int k = 0; k < 8; k++) *(uint4*)(dst + k * 2048 + t * 16) = norm_chunk(k, i0, -COFF, i1, -COFF);
        *(float2*)(dst + 16384 + t * 8) = make_float2(m0 + lg2(L0), m1 + lg2(L1));
        bar_arrive(6 + wg, 160);
        const float2 mm = lds2(sb + SM_M2 + wg * 1024 + t * 8);
        m0 = mm.x; m1 = mm.y;
        const float q0 = h_hi(__shfl_sync(~0u, Q[30], lane | 3)), q1 = h_hi(__shfl_sync(~0u, Q[31], lane | 3));
        sticky = __any_sync(~0u, m0 != -COFF * q0 || m1 != -COFF * q1);
        accz = 0;
      }
      if (sticky || fast()) exact();
    }
    PROBE(11 + wg);
    const bool finisher = isY || wg == 1;
    if (!finisher) {
      bar_sync(1 + wg, 256);
      pin(O); pin(P); wg_fence();
      issue_pv(st);
      wg_commit();
      bar_arrive(2, 256);
      wg_wait<0>(); pin(O);
      getL();
      const float i0 = L0 > 0.f ? COFF / L0 : 0.f, i1 = L1 > 0.f ? COFF / L1 : 0.f;
      const float c0 = L0 > 0.f ? -COFF : 0.f, c1 = L1 > 0.f ? -COFF : 0.f;
      const uint32_t dm = mapa(sb + SM_M + 16384 + t * 16, rank ^ 1), db = mapa(bars + 8 * B_M, rank ^ 1);
#pragma unroll
      for (int k = 0; k < 8; k++) { const uint4 v = norm_chunk(k, i0, c0, i1, c1); st_async4(dm + k * 2048, v.x, v.y, v.z, v.w, db); }
      st_async2(mapa(sb + SM_LAM + 1024 + t * 8, rank ^ 1), m0 + lg2(L0), m1 + lg2(L1), db);
      PROBE(13);
    } else {
      float Y[64];
      const int r0 = qfin * 128 + blk_fin * 64 + (t >> 5) * 16 + rr;
      uint4 xv[8];
#pragma unroll
      for (int i = 0; i < 8; i++) {
        const int r = r0 + (i >> 2) * 8;
        xv[i] = r < NN ? __ldg((const uint4*)x + r * 16 + (i & 3) * 4 + q) : make_uint4(0, 0, 0, 0);
      }
      int s1 = st + 1, p1 = ph; if (s1 == NST) { s1 = 0; p1 ^= 1; }
      int s2 = s1 + 1, p2 = p1; if (s2 == NST) { s2 = 0; p2 ^= 1; }
      mbar_wait(bars + 8 * B_G, 0);
      mbar_wait(bars + 8 * (B_FULL + s1), p1);
      bar_sync(1 + wg, 256);
      pin(O); pin(P); wg_fence();
      issue_pv(st);
      wg_commit();
#pragma unroll
      for (int ks = 0; ks < 8; ks++) mma_ss(Y, desc_k(sb + SM_G + wg * 16384) + koff(ks), desc_k(sb + SM_KV + s1 * TILE_B) + koff(ks), ks > 0);
      wg_commit();
      if (wg == 0) bar_arrive(2, 256);
      mbar_wait(bars + 8 * (B_FULL + s2), p2);
      mbar_wait_cluster(bars + 8 * B_M, 0);
      const float2 lo = lds2(sb + SM_LAM + wg * 1024 + t * 8);
      wg_wait<1>(); pin(O); pin(P);
      PROBE(14 + wg);
      getL();
      const float w0 = 1.f / (1.f + ex2(lo.x - m0 - lg2(L0))), w1 = 1.f / (1.f + ex2(lo.y - m1 - lg2(L1)));
      const float i0 = L0 > 0.f ? w0 * COFF / L0 : 0.f, i1 = L1 > 0.f ? w1 * COFF / L1 : 0.f;
      const float c0 = -COFF * w0, c1 = -COFF * w1, b0 = 1.f - w0, b1 = 1.f - w1;
#pragma unroll
      for (int k = 0; k < 8; k++) {
        const uint4 v = lds4(sb + SM_M + wg * 16384 + k * 2048 + t * 16);
        P[4 * k] = pack_bf16(fmaf(h_lo(v.x), b0, fmaf(O[8 * k], i0, c0)), fmaf(h_hi(v.x), b0, fmaf(O[8 * k + 1], i0, c0)));
        P[4 * k + 1] = pack_bf16(fmaf(h_lo(v.y), b1, fmaf(O[8 * k + 2], i1, c1)), fmaf(h_hi(v.y), b1, fmaf(O[8 * k + 3], i1, c1)));
        P[4 * k + 2] = pack_bf16(fmaf(h_lo(v.z), b0, fmaf(O[8 * k + 4], i0, c0)), fmaf(h_hi(v.z), b0, fmaf(O[8 * k + 5], i0, c0)));
        P[4 * k + 3] = pack_bf16(fmaf(h_lo(v.w), b1, fmaf(O[8 * k + 6], i1, c1)), fmaf(h_hi(v.w), b1, fmaf(O[8 * k + 7], i1, c1)));
      }
      pin(P); wg_fence();
#pragma unroll
      for (int ks = 0; ks < 8; ks++) mma_rs(Y, P[4 * ks], P[4 * ks + 1], P[4 * ks + 2], P[4 * ks + 3], desc_k(sb + SM_KV + s2 * TILE_B) + koff(ks), 1);
      wg_commit(); wg_wait<0>(); pin(Y);
#pragma unroll
      for (int i = 0; i < 8; i++) {
        const int h = i >> 2, I = i & 3, r = r0 + h * 8;
        const uint4 u = xv[i];
        uint4 o;
        o.x = pack_bf16(bf_lo(u.x) + Y[16 * I + 2 * h], bf_hi(u.x) + Y[16 * I + 2 * h + 1]);
        o.y = pack_bf16(bf_lo(u.y) + Y[16 * I + 4 + 2 * h], bf_hi(u.y) + Y[16 * I + 4 + 2 * h + 1]);
        o.z = pack_bf16(bf_lo(u.z) + Y[16 * I + 8 + 2 * h], bf_hi(u.z) + Y[16 * I + 8 + 2 * h + 1]);
        o.w = pack_bf16(bf_lo(u.w) + Y[16 * I + 12 + 2 * h], bf_hi(u.w) + Y[16 * I + 12 + 2 * h + 1]);
        if (r < NN) *((uint4*)out + r * 16 + I * 4 + q) = o;
      }
      PROBE(16 + wg);
    }
  }
}

}

extern "C" void kernel_launch(void* const* d_in, const int* in_sizes, int n_in, void* d_out, int out_size) {
  (void)in_sizes; (void)n_in; (void)out_size;
  cudaFuncSetAttribute(graphgps_kernel, cudaFuncAttributeMaxDynamicSharedMemorySize, SM_TOTAL);
  graphgps_kernel<<<NCTA, 384, SM_TOTAL>>>(
      (const __nv_bfloat16*)d_in[0], (const int*)d_in[1], (const int*)d_in[2], (const __nv_bfloat16*)d_in[3],
      (const __nv_bfloat16*)d_in[4], (const __nv_bfloat16*)d_in[5], (const __nv_bfloat16*)d_in[6],
      (const __nv_bfloat16*)d_in[7], (const __nv_bfloat16*)d_in[8], (__nv_bfloat16*)d_out);
}
```

```cpp
#include <cuda_runtime.h>
#include <cuda_bf16.h>
#include <cuda_fp16.h>
#include <stdint.h>

namespace {

constexpr int NCTA = 132;
constexpr int NN = 10000;
constexpr int EE = 160000;
constexpr int NPAD = 10112;
constexpr int T = 144;
constexpr int NST = 4;
constexpr uint32_t TILE_B = T * 256;
constexpr int OWG = 4;
constexpr int SPL = 3;
constexpr int JPARK = 4;
constexpr int KSA = 4;
constexpr int CAP = 48;
constexpr int EPC = 1216;
constexpr int NBIN = 158;
constexpr int BIN_B = NCTA * 64;
constexpr int LROW = 8 + 2 * CAP;
constexpr float COFF = 10.f;
constexpr float RS1 = 0.09695833f;
constexpr float RSN = 0.08838835f;
constexpr float QSCALE = 0.12751744f;
constexpr float QUP = 1.0024f;
constexpr float PSH = 2.f;
constexpr int SPIN = 1 << 22;

constexpr uint32_t SM_KV = 0;
constexpr uint32_t SM_G = NST * TILE_B;
constexpr uint32_t SM_M = SM_G + 32768;
constexpr uint32_t SM_LAM = SM_M + 32768;
constexpr uint32_t SM_ST = SM_LAM + 2048;
constexpr uint32_t SM_M2 = SM_ST + 1024;
constexpr uint32_t SM_BAR = SM_M2 + 1024;
constexpr uint32_t SM_ELL = SM_BAR + 512;
constexpr uint32_t SM_CNT = SM_ELL + NBIN * 64;
constexpr uint32_t SM_TOTAL = SM_CNT + 640 + 1024;
static_assert(SM_TOTAL <= 232448, "smem");
enum { B_FULL = 0, B_EMPTY = NST, B_WZ = 2 * NST, B_WFREE, B_G, B_M, B_Q2, B_E, B_X, B_X2, B_SC, B_MB, B_PAD, B_A, B_TAG };
static_assert(KSA == 4, "tile 0 is split at 64 keys");
static_assert(SM_ST % 1024 == 0, "state slots");
static_assert(B_TAG % 2 == 0, "16-byte slot");

constexpr int PART_B = 16384 + 1024;

__device__ __align__(1024) uint8_t g_h[NPAD * 256];
__device__ __align__(1024) uint8_t g_hp_raw[(1 << 24) + (NPAD + 1) * 256];
__device__ uint2 g_ovf[EE];
__device__ unsigned g_novf[2];
__device__ __align__(1024) uint8_t g_part[26 * 2 * 2 * PART_B];
__device__ __align__(1024) uint8_t g_wc[2 * 32768];
__device__ unsigned g_hflag[160 * 32];
__device__ unsigned g_pflag[26 * 4];
constexpr int OUT_MRG = NBIN * BIN_B, OUT_GX = OUT_MRG + 26 * 2 * PART_B, GX_IN = (NN * 256 - OUT_GX) / 8192;
__device__ __align__(1024) uint8_t g_gx2[(52 - GX_IN) * 8192];
__device__ unsigned g_mflag[26 * 4];
__device__ unsigned g_wflag[2];
__device__ int g_wexp;
__device__ __align__(16) unsigned long long g_epoch[2];
__device__ unsigned long long g_ellctr;
__device__ __align__(128) unsigned long long g_endctr;

__device__ __forceinline__ void mma_qk(float (&d)[72], uint32_t a0, uint32_t a1, uint32_t a2, uint32_t a3, uint64_t db, int scale_d) {
  asm volatile("{\n.reg .pred p;\nsetp.ne.b32 p, %77, 0;\n"
    "wgmma.mma_async.sync.aligned.m64n144k16.f32.f16.f16 {"
    "%0, %1, %2, %3, %4, %5, %6, %7, %8, %9, %10, %11, %12, %13, %14, %15, "
    "%16, %17, %18, %19, %20, %21, %22, %23, %24, %25, %26, %27, %28, %29, %30, %31, "
    "%32, %33, %34, %35, %36, %37, %38, %39, %40, %41, %42, %43, %44, %45, %46, %47, "
    "%48, %49, %50, %51, %52, %53, %54, %55, %56, %57, %58, %59, %60, %61, %62, %63, "
    "%64, %65, %66, %67, %68, %69, %70, %71}, "
    "{%72, %73, %74, %75}, %76, p, 1, 1, 0;\n}\n"
    : "+f"(d[0]), "+f"(d[1]), "+f"(d[2]), "+f"(d[3]), "+f"(d[4]), "+f"(d[5]), "+f"(d[6]), "+f"(d[7]),
      "+f"(d[8]), "+f"(d[9]), "+f"(d[10]), "+f"(d[11]), "+f"(d[12]), "+f"(d[13]), "+f"(d[14]), "+f"(d[15]),
      "+f"(d[16]), "+f"(d[17]), "+f"(d[18]), "+f"(d[19]), "+f"(d[20]), "+f"(d[21]), "+f"(d[22]), "+f"(d[23]),
      "+f"(d[24]), "+f"(d[25]), "+f"(d[26]), "+f"(d[27]), "+f"(d[28]), "+f"(d[29]), "+f"(d[30]), "+f"(d[31]),
      "+f"(d[32]), "+f"(d[33]), "+f"(d[34]), "+f"(d[35]), "+f"(d[36]), "+f"(d[37]), "+f"(d[38]), "+f"(d[39]),
      "+f"(d[40]), "+f"(d[41]), "+f"(d[42]), "+f"(d[43]), "+f"(d[44]), "+f"(d[45]), "+f"(d[46]), "+f"(d[47]),
      "+f"(d[48]), "+f"(d[49]), "+f"(d[50]), "+f"(d[51]), "+f"(d[52]), "+f"(d[53]), "+f"(d[54]), "+f"(d[55]),
      "+f"(d[56]), "+f"(d[57]), "+f"(d[58]), "+f"(d[59]), "+f"(d[60]), "+f"(d[61]), "+f"(d[62]), "+f"(d[63]),
      "+f"(d[64]), "+f"(d[65]), "+f"(d[66]), "+f"(d[67]), "+f"(d[68]), "+f"(d[69]), "+f"(d[70]), "+f"(d[71])
    : "r"(a0), "r"(a1), "r"(a2), "r"(a3), "l"(db), "r"(scale_d));
}
__device__ __forceinline__ void mma_qk_z(float (&d)[72], uint32_t a0, uint32_t a1, uint32_t a2, uint32_t a3, uint64_t db) {
  asm volatile("{\n.reg .pred p;\nsetp.ne.b32 p, 0, 0;\n"
    "wgmma.mma_async.sync.aligned.m64n144k16.f32.f16.f16 {"
    "%0, %1, %2, %3, %4, %5, %6, %7, %8, %9, %10, %11, %12, %13, %14, %15, "
    "%16, %17, %18, %19, %20, %21, %22, %23, %24, %25, %26, %27, %28, %29, %30, %31, "
    "%32, %33, %34, %35, %36, %37, %38, %39, %40, %41, %42, %43, %44, %45, %46, %47, "
    "%48, %49, %50, %51, %52, %53, %54, %55, %56, %57, %58, %59, %60, %61, %62, %63, "
    "%64, %65, %66, %67, %68, %69, %70, %71}, "
    "{%72, %73, %74, %75}, %76, p, 1, 1, 0;\n}\n"
    : "=f"(d[0]), "=f"(d[1]), "=f"(d[2]), "=f"(d[3]), "=f"(d[4]), "=f"(d[5]), "=f"(d[6]), "=f"(d[7]),
      "=f"(d[8]), "=f"(d[9]), "=f"(d[10]), "=f"(d[11]), "=f"(d[12]), "=f"(d[13]), "=f"(d[14]), "=f"(d[15]),
      "=f"(d[16]), "=f"(d[17]), "=f"(d[18]), "=f"(d[19]), "=f"(d[20]), "=f"(d[21]), "=f"(d[22]), "=f"(d[23]),
      "=f"(d[24]), "=f"(d[25]), "=f"(d[26]), "=f"(d[27]), "=f"(d[28]), "=f"(d[29]), "=f"(d[30]), "=f"(d[31]),
      "=f"(d[32]), "=f"(d[33]), "=f"(d[34]), "=f"(d[35]), "=f"(d[36]), "=f"(d[37]), "=f"(d[38]), "=f"(d[39]),
      "=f"(d[40]), "=f"(d[41]), "=f"(d[42]), "=f"(d[43]), "=f"(d[44]), "=f"(d[45]), "=f"(d[46]), "=f"(d[47]),
      "=f"(d[48]), "=f"(d[49]), "=f"(d[50]), "=f"(d[51]), "=f"(d[52]), "=f"(d[53]), "=f"(d[54]), "=f"(d[55]),
      "=f"(d[56]), "=f"(d[57]), "=f"(d[58]), "=f"(d[59]), "=f"(d[60]), "=f"(d[61]), "=f"(d[62]), "=f"(d[63]),
      "=f"(d[64]), "=f"(d[65]), "=f"(d[66]), "=f"(d[67]), "=f"(d[68]), "=f"(d[69]), "=f"(d[70]), "=f"(d[71])
    : "r"(a0), "r"(a1), "r"(a2), "r"(a3), "l"(db));
}
__device__ __forceinline__ void mma_qk(float (&d)[64], uint32_t a0, uint32_t a1, uint32_t a2, uint32_t a3, uint64_t db, int scale_d) {
  asm volatile("{\n.reg .pred p;\nsetp.ne.b32 p, %69, 0;\n"
    "wgmma.mma_async.sync.aligned.m64n128k16.f32.f16.f16 {"
    "%0, %1, %2, %3, %4, %5, %6, %7, %8, %9, %10, %11, %12, %13, %14, %15, "
    "%16, %17, %18, %19, %20, %21, %22, %23, %24, %25, %26, %27, %28, %29, %30, %31, "
    "%32, %33, %34, %35, %36, %37, %38, %39, %40, %41, %42, %43, %44, %45, %46, %47, "
    "%48, %49, %50, %51, %52, %53, %54, %55, %56, %57, %58, %59, %60, %61, %62, %63}, "
    "{%64, %65, %66, %67}, %68, p, 1, 1, 0;\n}\n"
    : "+f"(d[0]), "+f"(d[1]), "+f"(d[2]), "+f"(d[3]), "+f"(d[4]), "+f"(d[5]), "+f"(d[6]), "+f"(d[7]),
      "+f"(d[8]), "+f"(d[9]), "+f"(d[10]), "+f"(d[11]), "+f"(d[12]), "+f"(d[13]), "+f"(d[14]), "+f"(d[15]),
      "+f"(d[16]), "+f"(d[17]), "+f"(d[18]), "+f"(d[19]), "+f"(d[20]), "+f"(d[21]), "+f"(d[22]), "+f"(d[23]),
      "+f"(d[24]), "+f"(d[25]), "+f"(d[26]), "+f"(d[27]), "+f"(d[28]), "+f"(d[29]), "+f"(d[30]), "+f"(d[31]),
      "+f"(d[32]), "+f"(d[33]), "+f"(d[34]), "+f"(d[35]), "+f"(d[36]), "+f"(d[37]), "+f"(d[38]), "+f"(d[39]),
      "+f"(d[40]), "+f"(d[41]), "+f"(d[42]), "+f"(d[43]), "+f"(d[44]), "+f"(d[45]), "+f"(d[46]), "+f"(d[47]),
      "+f"(d[48]), "+f"(d[49]), "+f"(d[50]), "+f"(d[51]), "+f"(d[52]), "+f"(d[53]), "+f"(d[54]), "+f"(d[55]),
      "+f"(d[56]), "+f"(d[57]), "+f"(d[58]), "+f"(d[59]), "+f"(d[60]), "+f"(d[61]), "+f"(d[62]), "+f"(d[63])
    : "r"(a0), "r"(a1), "r"(a2), "r"(a3), "l"(db), "r"(scale_d));
}
__device__ __forceinline__ void mma_qk(float (&d)[32], uint32_t a0, uint32_t a1, uint32_t a2, uint32_t a3, uint64_t db, int scale_d) {
  asm volatile("{\n.reg .pred p;\nsetp.ne.b32 p, %37, 0;\n"
    "wgmma.mma_async.sync.aligned.m64n64k16.f32.f16.f16 {"
    "%0, %1, %2, %3, %4, %5, %6, %7, %8, %9, %10, %11, %12, %13, %14, %15, "
    "%16, %17, %18, %19, %20, %21, %22, %23, %24, %25, %26, %27, %28, %29, %30, %31}, "
    "{%32, %33, %34, %35}, %36, p, 1, 1, 0;\n}\n"
    : "+f"(d[0]), "+f"(d[1]), "+f"(d[2]), "+f"(d[3]), "+f"(d[4]), "+f"(d[5]), "+f"(d[6]), "+f"(d[7]),
      "+f"(d[8]), "+f"(d[9]), "+f"(d[10]), "+f"(d[11]), "+f"(d[12]), "+f"(d[13]), "+f"(d[14]), "+f"(d[15]),
      "+f"(d[16]), "+f"(d[17]), "+f"(d[18]), "+f"(d[19]), "+f"(d[20]), "+f"(d[21]), "+f"(d[22]), "+f"(d[23]),
      "+f"(d[24]), "+f"(d[25]), "+f"(d[26]), "+f"(d[27]), "+f"(d[28]), "+f"(d[29]), "+f"(d[30]), "+f"(d[31])
    : "r"(a0), "r"(a1), "r"(a2), "r"(a3), "l"(db), "r"(scale_d));
}
__device__ __forceinline__ void mma_qk_z(float (&d)[32], uint32_t a0, uint32_t a1, uint32_t a2, uint32_t a3, uint64_t db) {
  asm volatile("{\n.reg .pred p;\nsetp.ne.b32 p, 0, 0;\n"
    "wgmma.mma_async.sync.aligned.m64n64k16.f32.f16.f16 {"
    "%0, %1, %2, %3, %4, %5, %6, %7, %8, %9, %10, %11, %12, %13, %14, %15, "
    "%16, %17, %18, %19, %20, %21, %22, %23, %24, %25, %26, %27, %28, %29, %30, %31}, "
    "{%32, %33, %34, %35}, %36, p, 1, 1, 0;\n}\n"
    : "=f"(d[0]), "=f"(d[1]), "=f"(d[2]), "=f"(d[3]), "=f"(d[4]), "=f"(d[5]), "=f"(d[6]), "=f"(d[7]),
      "=f"(d[8]), "=f"(d[9]), "=f"(d[10]), "=f"(d[11]), "=f"(d[12]), "=f"(d[13]), "=f"(d[14]), "=f"(d[15]),
      "=f"(d[16]), "=f"(d[17]), "=f"(d[18]), "=f"(d[19]), "=f"(d[20]), "=f"(d[21]), "=f"(d[22]), "=f"(d[23]),
      "=f"(d[24]), "=f"(d[25]), "=f"(d[26]), "=f"(d[27]), "=f"(d[28]), "=f"(d[29]), "=f"(d[30]), "=f"(d[31])
    : "r"(a0), "r"(a1), "r"(a2), "r"(a3), "l"(db));
}
__device__ __forceinline__ void mma_qk(float (&d)[40], uint32_t a0, uint32_t a1, uint32_t a2, uint32_t a3, uint64_t db, int scale_d) {
  asm volatile("{\n.reg .pred p;\nsetp.ne.b32 p, %45, 0;\n"
    "wgmma.mma_async.sync.aligned.m64n80k16.f32.f16.f16 {"
    "%0, %1, %2, %3, %4, %5, %6, %7, %8, %9, %10, %11, %12, %13, %14, %15, "
    "%16, %17, %18, %19, %20, %21, %22, %23, %24, %25, %26, %27, %28, %29, %30, %31, "
    "%32, %33, %34, %35, %36, %37, %38, %39}, "
    "{%40, %41, %42, %43}, %44, p, 1, 1, 0;\n}\n"
    : "+f"(d[0]), "+f"(d[1]), "+f"(d[2]), "+f"(d[3]), "+f"(d[4]), "+f"(d[5]), "+f"(d[6]), "+f"(d[7]),
      "+f"(d[8]), "+f"(d[9]), "+f"(d[10]), "+f"(d[11]), "+f"(d[12]), "+f"(d[13]), "+f"(d[14]), "+f"(d[15]),
      "+f"(d[16]), "+f"(d[17]), "+f"(d[18]), "+f"(d[19]), "+f"(d[20]), "+f"(d[21]), "+f"(d[22]), "+f"(d[23]),
      "+f"(d[24]), "+f"(d[25]), "+f"(d[26]), "+f"(d[27]), "+f"(d[28]), "+f"(d[29]), "+f"(d[30]), "+f"(d[31]),
      "+f"(d[32]), "+f"(d[33]), "+f"(d[34]), "+f"(d[35]), "+f"(d[36]), "+f"(d[37]), "+f"(d[38]), "+f"(d[39])
    : "r"(a0), "r"(a1), "r"(a2), "r"(a3), "l"(db), "r"(scale_d));
}
__device__ __forceinline__ void mma_qk_z(float (&d)[40], uint32_t a0, uint32_t a1, uint32_t a2, uint32_t a3, uint64_t db) {
  asm volatile("{\n.reg .pred p;\nsetp.ne.b32 p, 0, 0;\n"
    "wgmma.mma_async.sync.aligned.m64n80k16.f32.f16.f16 {"
    "%0, %1, %2, %3, %4, %5, %6, %7, %8, %9, %10, %11, %12, %13, %14, %15, "
    "%16, %17, %18, %19, %20, %21, %22, %23, %24, %25, %26, %27, %28, %29, %30, %31, "
    "%32, %33, %34, %35, %36, %37, %38, %39}, "
    "{%40, %41, %42, %43}, %44, p, 1, 1, 0;\n}\n"
    : "=f"(d[0]), "=f"(d[1]), "=f"(d[2]), "=f"(d[3]), "=f"(d[4]), "=f"(d[5]), "=f"(d[6]), "=f"(d[7]),
      "=f"(d[8]), "=f"(d[9]), "=f"(d[10]), "=f"(d[11]), "=f"(d[12]), "=f"(d[13]), "=f"(d[14]), "=f"(d[15]),
      "=f"(d[16]), "=f"(d[17]), "=f"(d[18]), "=f"(d[19]), "=f"(d[20]), "=f"(d[21]), "=f"(d[22]), "=f"(d[23]),
      "=f"(d[24]), "=f"(d[25]), "=f"(d[26]), "=f"(d[27]), "=f"(d[28]), "=f"(d[29]), "=f"(d[30]), "=f"(d[31]),
      "=f"(d[32]), "=f"(d[33]), "=f"(d[34]), "=f"(d[35]), "=f"(d[36]), "=f"(d[37]), "=f"(d[38]), "=f"(d[39])
    : "r"(a0), "r"(a1), "r"(a2), "r"(a3), "l"(db));
}
__device__ __forceinline__ void mma_qk(float (&d)[56], uint32_t a0, uint32_t a1, uint32_t a2, uint32_t a3, uint64_t db, int scale_d) {
  asm volatile("{\n.reg .pred p;\nsetp.ne.b32 p, %61, 0;\n"
    "wgmma.mma_async.sync.aligned.m64n112k16.f32.f16.f16 {"
    "%0, %1, %2, %3, %4, %5, %6, %7, %8, %9, %10, %11, %12, %13, %14, %15, "
    "%16, %17, %18, %19, %20, %21, %22, %23, %24, %25, %26, %27, %28, %29, %30, %31, "
    "%32, %33, %34, %35, %36, %37, %38, %39, %40, %41, %42, %43, %44, %45, %46, %47, "
    "%48, %49, %50, %51, %52, %53, %54, %55}, "
    "{%56, %57, %58, %59}, %60, p, 1, 1, 0;\n}\n"
    : "+f"(d[0]), "+f"(d[1]), "+f"(d[2]), "+f"(d[3]), "+f"(d[4]), "+f"(d[5]), "+f"(d[6]), "+f"(d[7]),
      "+f"(d[8]), "+f"(d[9]), "+f"(d[10]), "+f"(d[11]), "+f"(d[12]), "+f"(d[13]), "+f"(d[14]), "+f"(d[15]),
      "+f"(d[16]), "+f"(d[17]), "+f"(d[18]), "+f"(d[19]), "+f"(d[20]), "+f"(d[21]), "+f"(d[22]), "+f"(d[23]),
      "+f"(d[24]), "+f"(d[25]), "+f"(d[26]), "+f"(d[27]), "+f"(d[28]), "+f"(d[29]), "+f"(d[30]), "+f"(d[31]),
      "+f"(d[32]), "+f"(d[33]), "+f"(d[34]), "+f"(d[35]), "+f"(d[36]), "+f"(d[37]), "+f"(d[38]), "+f"(d[39]),
      "+f"(d[40]), "+f"(d[41]), "+f"(d[42]), "+f"(d[43]), "+f"(d[44]), "+f"(d[45]), "+f"(d[46]), "+f"(d[47]),
      "+f"(d[48]), "+f"(d[49]), "+f"(d[50]), "+f"(d[51]), "+f"(d[52]), "+f"(d[53]), "+f"(d[54]), "+f"(d[55])
    : "r"(a0), "r"(a1), "r"(a2), "r"(a3), "l"(db), "r"(scale_d));
}
__device__ __forceinline__ void mma_qk_z(float (&d)[56], uint32_t a0, uint32_t a1, uint32_t a2, uint32_t a3, uint64_t db) {
  asm volatile("{\n.reg .pred p;\nsetp.ne.b32 p, 0, 0;\n"
    "wgmma.mma_async.sync.aligned.m64n112k16.f32.f16.f16 {"
    "%0, %1, %2, %3, %4, %5, %6, %7, %8, %9, %10, %11, %12, %13, %14, %15, "
    "%16, %17, %18, %19, %20, %21, %22, %23, %24, %25, %26, %27, %28, %29, %30, %31, "
    "%32, %33, %34, %35, %36, %37, %38, %39, %40, %41, %42, %43, %44, %45, %46, %47, "
    "%48, %49, %50, %51, %52, %53, %54, %55}, "
    "{%56, %57, %58, %59}, %60, p, 1, 1, 0;\n}\n"
    : "=f"(d[0]), "=f"(d[1]), "=f"(d[2]), "=f"(d[3]), "=f"(d[4]), "=f"(d[5]), "=f"(d[6]), "=f"(d[7]),
      "=f"(d[8]), "=f"(d[9]), "=f"(d[10]), "=f"(d[11]), "=f"(d[12]), "=f"(d[13]), "=f"(d[14]), "=f"(d[15]),
      "=f"(d[16]), "=f"(d[17]), "=f"(d[18]), "=f"(d[19]), "=f"(d[20]), "=f"(d[21]), "=f"(d[22]), "=f"(d[23]),
      "=f"(d[24]), "=f"(d[25]), "=f"(d[26]), "=f"(d[27]), "=f"(d[28]), "=f"(d[29]), "=f"(d[30]), "=f"(d[31]),
      "=f"(d[32]), "=f"(d[33]), "=f"(d[34]), "=f"(d[35]), "=f"(d[36]), "=f"(d[37]), "=f"(d[38]), "=f"(d[39]),
      "=f"(d[40]), "=f"(d[41]), "=f"(d[42]), "=f"(d[43]), "=f"(d[44]), "=f"(d[45]), "=f"(d[46]), "=f"(d[47]),
      "=f"(d[48]), "=f"(d[49]), "=f"(d[50]), "=f"(d[51]), "=f"(d[52]), "=f"(d[53]), "=f"(d[54]), "=f"(d[55])
    : "r"(a0), "r"(a1), "r"(a2), "r"(a3), "l"(db));
}
__device__ __forceinline__ void mma_pv(float (&d)[64], uint32_t a0, uint32_t a1, uint32_t a2, uint32_t a3, uint64_t db, int scale_d) {
  asm volatile("{\n.reg .pred p;\nsetp.ne.b32 p, %69, 0;\n"
    "wgmma.mma_async.sync.aligned.m64n128k16.f32.f16.f16 {"
    "%0, %1, %2, %3, %4, %5, %6, %7, %8, %9, %10, %11, %12, %13, %14, %15, "
    "%16, %17, %18, %19, %20, %21, %22, %23, %24, %25, %26, %27, %28, %29, %30, %31, "
    "%32, %33, %34, %35, %36, %37, %38, %39, %40, %41, %42, %43, %44, %45, %46, %47, "
    "%48, %49, %50, %51, %52, %53, %54, %55, %56, %57, %58, %59, %60, %61, %62, %63}, "
    "{%64, %65, %66, %67}, %68, p, 1, 1, 1;\n}\n"
    : "+f"(d[0]), "+f"(d[1]), "+f"(d[2]), "+f"(d[3]), "+f"(d[4]), "+f"(d[5]), "+f"(d[6]), "+f"(d[7]),
      "+f"(d[8]), "+f"(d[9]), "+f"(d[10]), "+f"(d[11]), "+f"(d[12]), "+f"(d[13]), "+f"(d[14]), "+f"(d[15]),
      "+f"(d[16]), "+f"(d[17]), "+f"(d[18]), "+f"(d[19]), "+f"(d[20]), "+f"(d[21]), "+f"(d[22]), "+f"(d[23]),
      "+f"(d[24]), "+f"(d[25]), "+f"(d[26]), "+f"(d[27]), "+f"(d[28]), "+f"(d[29]), "+f"(d[30]), "+f"(d[31]),
      "+f"(d[32]), "+f"(d[33]), "+f"(d[34]), "+f"(d[35]), "+f"(d[36]), "+f"(d[37]), "+f"(d[38]), "+f"(d[39]),
      "+f"(d[40]), "+f"(d[41]), "+f"(d[42]), "+f"(d[43]), "+f"(d[44]), "+f"(d[45]), "+f"(d[46]), "+f"(d[47]),
      "+f"(d[48]), "+f"(d[49]), "+f"(d[50]), "+f"(d[51]), "+f"(d[52]), "+f"(d[53]), "+f"(d[54]), "+f"(d[55]),
      "+f"(d[56]), "+f"(d[57]), "+f"(d[58]), "+f"(d[59]), "+f"(d[60]), "+f"(d[61]), "+f"(d[62]), "+f"(d[63])
    : "r"(a0), "r"(a1), "r"(a2), "r"(a3), "l"(db), "r"(scale_d));
}
__device__ __forceinline__ void mma_pv_z(float (&d)[64], uint32_t a0, uint32_t a1, uint32_t a2, uint32_t a3, uint64_t db) {
  asm volatile("{\n.reg .pred p;\nsetp.ne.b32 p, 0, 0;\n"
    "wgmma.mma_async.sync.aligned.m64n128k16.f32.f16.f16 {"
    "%0, %1, %2, %3, %4, %5, %6, %7, %8, %9, %10, %11, %12, %13, %14, %15, "
    "%16, %17, %18, %19, %20, %21, %22, %23, %24, %25, %26, %27, %28, %29, %30, %31, "
    "%32, %33, %34, %35, %36, %37, %38, %39, %40, %41, %42, %43, %44, %45, %46, %47, "
    "%48, %49, %50, %51, %52, %53, %54, %55, %56, %57, %58, %59, %60, %61, %62, %63}, "
    "{%64, %65, %66, %67}, %68, p, 1, 1, 1;\n}\n"
    : "=f"(d[0]), "=f"(d[1]), "=f"(d[2]), "=f"(d[3]), "=f"(d[4]), "=f"(d[5]), "=f"(d[6]), "=f"(d[7]),
      "=f"(d[8]), "=f"(d[9]), "=f"(d[10]), "=f"(d[11]), "=f"(d[12]), "=f"(d[13]), "=f"(d[14]), "=f"(d[15]),
      "=f"(d[16]), "=f"(d[17]), "=f"(d[18]), "=f"(d[19]), "=f"(d[20]), "=f"(d[21]), "=f"(d[22]), "=f"(d[23]),
      "=f"(d[24]), "=f"(d[25]), "=f"(d[26]), "=f"(d[27]), "=f"(d[28]), "=f"(d[29]), "=f"(d[30]), "=f"(d[31]),
      "=f"(d[32]), "=f"(d[33]), "=f"(d[34]), "=f"(d[35]), "=f"(d[36]), "=f"(d[37]), "=f"(d[38]), "=f"(d[39]),
      "=f"(d[40]), "=f"(d[41]), "=f"(d[42]), "=f"(d[43]), "=f"(d[44]), "=f"(d[45]), "=f"(d[46]), "=f"(d[47]),
      "=f"(d[48]), "=f"(d[49]), "=f"(d[50]), "=f"(d[51]), "=f"(d[52]), "=f"(d[53]), "=f"(d[54]), "=f"(d[55]),
      "=f"(d[56]), "=f"(d[57]), "=f"(d[58]), "=f"(d[59]), "=f"(d[60]), "=f"(d[61]), "=f"(d[62]), "=f"(d[63])
    : "r"(a0), "r"(a1), "r"(a2), "r"(a3), "l"(db));
}
__device__ __forceinline__ void mma_rs_t(float (&d)[64], uint32_t a0, uint32_t a1, uint32_t a2, uint32_t a3, uint64_t db, int scale_d) {
  asm volatile("{\n.reg .pred p;\nsetp.ne.b32 p, %69, 0;\n"
    "wgmma.mma_async.sync.aligned.m64n128k16.f32.bf16.bf16 {"
    "%0, %1, %2, %3, %4, %5, %6, %7, %8, %9, %10, %11, %12, %13, %14, %15, "
    "%16, %17, %18, %19, %20, %21, %22, %23, %24, %25, %26, %27, %28, %29, %30, %31, "
    "%32, %33, %34, %35, %36, %37, %38, %39, %40, %41, %42, %43, %44, %45, %46, %47, "
    "%48, %49, %50, %51, %52, %53, %54, %55, %56, %57, %58, %59, %60, %61, %62, %63}, "
    "{%64, %65, %66, %67}, %68, p, 1, 1, 1;\n}\n"
    : "+f"(d[0]), "+f"(d[1]), "+f"(d[2]), "+f"(d[3]), "+f"(d[4]), "+f"(d[5]), "+f"(d[6]), "+f"(d[7]),
      "+f"(d[8]), "+f"(d[9]), "+f"(d[10]), "+f"(d[11]), "+f"(d[12]), "+f"(d[13]), "+f"(d[14]), "+f"(d[15]),
      "+f"(d[16]), "+f"(d[17]), "+f"(d[18]), "+f"(d[19]), "+f"(d[20]), "+f"(d[21]), "+f"(d[22]), "+f"(d[23]),
      "+f"(d[24]), "+f"(d[25]), "+f"(d[26]), "+f"(d[27]), "+f"(d[28]), "+f"(d[29]), "+f"(d[30]), "+f"(d[31]),
      "+f"(d[32]), "+f"(d[33]), "+f"(d[34]), "+f"(d[35]), "+f"(d[36]), "+f"(d[37]), "+f"(d[38]), "+f"(d[39]),
      "+f"(d[40]), "+f"(d[41]), "+f"(d[42]), "+f"(d[43]), "+f"(d[44]), "+f"(d[45]), "+f"(d[46]), "+f"(d[47]),
      "+f"(d[48]), "+f"(d[49]), "+f"(d[50]), "+f"(d[51]), "+f"(d[52]), "+f"(d[53]), "+f"(d[54]), "+f"(d[55]),
      "+f"(d[56]), "+f"(d[57]), "+f"(d[58]), "+f"(d[59]), "+f"(d[60]), "+f"(d[61]), "+f"(d[62]), "+f"(d[63])
    : "r"(a0), "r"(a1), "r"(a2), "r"(a3), "l"(db), "r"(scale_d));
}
__device__ __forceinline__ void mma_rs_t_z(float (&d)[64], uint32_t a0, uint32_t a1, uint32_t a2, uint32_t a3, uint64_t db) {
  asm volatile("{\n.reg .pred p;\nsetp.ne.b32 p, 0, 0;\n"
    "wgmma.mma_async.sync.aligned.m64n128k16.f32.bf16.bf16 {"
    "%0, %1, %2, %3, %4, %5, %6, %7, %8, %9, %10, %11, %12, %13, %14, %15, "
    "%16, %17, %18, %19, %20, %21, %22, %23, %24, %25, %26, %27, %28, %29, %30, %31, "
    "%32, %33, %34, %35, %36, %37, %38, %39, %40, %41, %42, %43, %44, %45, %46, %47, "
    "%48, %49, %50, %51, %52, %53, %54, %55, %56, %57, %58, %59, %60, %61, %62, %63}, "
    "{%64, %65, %66, %67}, %68, p, 1, 1, 1;\n}\n"
    : "=f"(d[0]), "=f"(d[1]), "=f"(d[2]), "=f"(d[3]), "=f"(d[4]), "=f"(d[5]), "=f"(d[6]), "=f"(d[7]),
      "=f"(d[8]), "=f"(d[9]), "=f"(d[10]), "=f"(d[11]), "=f"(d[12]), "=f"(d[13]), "=f"(d[14]), "=f"(d[15]),
      "=f"(d[16]), "=f"(d[17]), "=f"(d[18]), "=f"(d[19]), "=f"(d[20]), "=f"(d[21]), "=f"(d[22]), "=f"(d[23]),
      "=f"(d[24]), "=f"(d[25]), "=f"(d[26]), "=f"(d[27]), "=f"(d[28]), "=f"(d[29]), "=f"(d[30]), "=f"(d[31]),
      "=f"(d[32]), "=f"(d[33]), "=f"(d[34]), "=f"(d[35]), "=f"(d[36]), "=f"(d[37]), "=f"(d[38]), "=f"(d[39]),
      "=f"(d[40]), "=f"(d[41]), "=f"(d[42]), "=f"(d[43]), "=f"(d[44]), "=f"(d[45]), "=f"(d[46]), "=f"(d[47]),
      "=f"(d[48]), "=f"(d[49]), "=f"(d[50]), "=f"(d[51]), "=f"(d[52]), "=f"(d[53]), "=f"(d[54]), "=f"(d[55]),
      "=f"(d[56]), "=f"(d[57]), "=f"(d[58]), "=f"(d[59]), "=f"(d[60]), "=f"(d[61]), "=f"(d[62]), "=f"(d[63])
    : "r"(a0), "r"(a1), "r"(a2), "r"(a3), "l"(db));
}
__device__ __forceinline__ void mma_ss(float (&d)[64], uint64_t da, uint64_t db, int scale_d) {
  asm volatile("{\n.reg .pred p;\nsetp.ne.b32 p, %66, 0;\n"
    "wgmma.mma_async.sync.aligned.m64n128k16.f32.bf16.bf16 {"
    "%0, %1, %2, %3, %4, %5, %6, %7, %8, %9, %10, %11, %12, %13, %14, %15, "
    "%16, %17, %18, %19, %20, %21, %22, %23, %24, %25, %26, %27, %28, %29, %30, %31, "
    "%32, %33, %34, %35, %36, %37, %38, %39, %40, %41, %42, %43, %44, %45, %46, %47, "
    "%48, %49, %50, %51, %52, %53, %54, %55, %56, %57, %58, %59, %60, %61, %62, %63}, "
    "%64, %65, p, 1, 1, 0, 0;\n}\n"
    : "+f"(d[0]), "+f"(d[1]), "+f"(d[2]), "+f"(d[3]), "+f"(d[4]), "+f"(d[5]), "+f"(d[6]), "+f"(d[7]),
      "+f"(d[8]), "+f"(d[9]), "+f"(d[10]), "+f"(d[11]), "+f"(d[12]), "+f"(d[13]), "+f"(d[14]), "+f"(d[15]),
      "+f"(d[16]), "+f"(d[17]), "+f"(d[18]), "+f"(d[19]), "+f"(d[20]), "+f"(d[21]), "+f"(d[22]), "+f"(d[23]),
      "+f"(d[24]), "+f"(d[25]), "+f"(d[26]), "+f"(d[27]), "+f"(d[28]), "+f"(d[29]), "+f"(d[30]), "+f"(d[31]),
      "+f"(d[32]), "+f"(d[33]), "+f"(d[34]), "+f"(d[35]), "+f"(d[36]), "+f"(d[37]), "+f"(d[38]), "+f"(d[39]),
      "+f"(d[40]), "+f"(d[41]), "+f"(d[42]), "+f"(d[43]), "+f"(d[44]), "+f"(d[45]), "+f"(d[46]), "+f"(d[47]),
      "+f"(d[48]), "+f"(d[49]), "+f"(d[50]), "+f"(d[51]), "+f"(d[52]), "+f"(d[53]), "+f"(d[54]), "+f"(d[55]),
      "+f"(d[56]), "+f"(d[57]), "+f"(d[58]), "+f"(d[59]), "+f"(d[60]), "+f"(d[61]), "+f"(d[62]), "+f"(d[63])
    : "l"(da), "l"(db), "r"(scale_d));
}
__device__ __forceinline__ void mma_ss_z(float (&d)[64], uint64_t da, uint64_t db) {
  asm volatile("{\n.reg .pred p;\nsetp.ne.b32 p, 0, 0;\n"
    "wgmma.mma_async.sync.aligned.m64n128k16.f32.bf16.bf16 {"
    "%0, %1, %2, %3, %4, %5, %6, %7, %8, %9, %10, %11, %12, %13, %14, %15, "
    "%16, %17, %18, %19, %20, %21, %22, %23, %24, %25, %26, %27, %28, %29, %30, %31, "
    "%32, %33, %34, %35, %36, %37, %38, %39, %40, %41, %42, %43, %44, %45, %46, %47, "
    "%48, %49, %50, %51, %52, %53, %54, %55, %56, %57, %58, %59, %60, %61, %62, %63}, "
    "%64, %65, p, 1, 1, 0, 0;\n}\n"
    : "=f"(d[0]), "=f"(d[1]), "=f"(d[2]), "=f"(d[3]), "=f"(d[4]), "=f"(d[5]), "=f"(d[6]), "=f"(d[7]),
      "=f"(d[8]), "=f"(d[9]), "=f"(d[10]), "=f"(d[11]), "=f"(d[12]), "=f"(d[13]), "=f"(d[14]), "=f"(d[15]),
      "=f"(d[16]), "=f"(d[17]), "=f"(d[18]), "=f"(d[19]), "=f"(d[20]), "=f"(d[21]), "=f"(d[22]), "=f"(d[23]),
      "=f"(d[24]), "=f"(d[25]), "=f"(d[26]), "=f"(d[27]), "=f"(d[28]), "=f"(d[29]), "=f"(d[30]), "=f"(d[31]),
      "=f"(d[32]), "=f"(d[33]), "=f"(d[34]), "=f"(d[35]), "=f"(d[36]), "=f"(d[37]), "=f"(d[38]), "=f"(d[39]),
      "=f"(d[40]), "=f"(d[41]), "=f"(d[42]), "=f"(d[43]), "=f"(d[44]), "=f"(d[45]), "=f"(d[46]), "=f"(d[47]),
      "=f"(d[48]), "=f"(d[49]), "=f"(d[50]), "=f"(d[51]), "=f"(d[52]), "=f"(d[53]), "=f"(d[54]), "=f"(d[55]),
      "=f"(d[56]), "=f"(d[57]), "=f"(d[58]), "=f"(d[59]), "=f"(d[60]), "=f"(d[61]), "=f"(d[62]), "=f"(d[63])
    : "l"(da), "l"(db));
}
__device__ __forceinline__ void mma_ss_ta(float (&d)[64], uint64_t da, uint64_t db, int scale_d) {
  asm volatile("{\n.reg .pred p;\nsetp.ne.b32 p, %66, 0;\n"
    "wgmma.mma_async.sync.aligned.m64n128k16.f32.bf16.bf16 {"
    "%0, %1, %2, %3, %4, %5, %6, %7, %8, %9, %10, %11, %12, %13, %14, %15, "
    "%16, %17, %18, %19, %20, %21, %22, %23, %24, %25, %26, %27, %28, %29, %30, %31, "
    "%32, %33, %34, %35, %36, %37, %38, %39, %40, %41, %42, %43, %44, %45, %46, %47, "
    "%48, %49, %50, %51, %52, %53, %54, %55, %56, %57, %58, %59, %60, %61, %62, %63}, "
    "%64, %65, p, 1, 1, 1, 0;\n}\n"
    : "+f"(d[0]), "+f"(d[1]), "+f"(d[2]), "+f"(d[3]), "+f"(d[4]), "+f"(d[5]), "+f"(d[6]), "+f"(d[7]),
      "+f"(d[8]), "+f"(d[9]), "+f"(d[10]), "+f"(d[11]), "+f"(d[12]), "+f"(d[13]), "+f"(d[14]), "+f"(d[15]),
      "+f"(d[16]), "+f"(d[17]), "+f"(d[18]), "+f"(d[19]), "+f"(d[20]), "+f"(d[21]), "+f"(d[22]), "+f"(d[23]),
      "+f"(d[24]), "+f"(d[25]), "+f"(d[26]), "+f"(d[27]), "+f"(d[28]), "+f"(d[29]), "+f"(d[30]), "+f"(d[31]),
      "+f"(d[32]), "+f"(d[33]), "+f"(d[34]), "+f"(d[35]), "+f"(d[36]), "+f"(d[37]), "+f"(d[38]), "+f"(d[39]),
      "+f"(d[40]), "+f"(d[41]), "+f"(d[42]), "+f"(d[43]), "+f"(d[44]), "+f"(d[45]), "+f"(d[46]), "+f"(d[47]),
      "+f"(d[48]), "+f"(d[49]), "+f"(d[50]), "+f"(d[51]), "+f"(d[52]), "+f"(d[53]), "+f"(d[54]), "+f"(d[55]),
      "+f"(d[56]), "+f"(d[57]), "+f"(d[58]), "+f"(d[59]), "+f"(d[60]), "+f"(d[61]), "+f"(d[62]), "+f"(d[63])
    : "l"(da), "l"(db), "r"(scale_d));
}
__device__ __forceinline__ void mma_ss_ta_z(float (&d)[64], uint64_t da, uint64_t db) {
  asm volatile("{\n.reg .pred p;\nsetp.ne.b32 p, 0, 0;\n"
    "wgmma.mma_async.sync.aligned.m64n128k16.f32.bf16.bf16 {"
    "%0, %1, %2, %3, %4, %5, %6, %7, %8, %9, %10, %11, %12, %13, %14, %15, "
    "%16, %17, %18, %19, %20, %21, %22, %23, %24, %25, %26, %27, %28, %29, %30, %31, "
    "%32, %33, %34, %35, %36, %37, %38, %39, %40, %41, %42, %43, %44, %45, %46, %47, "
    "%48, %49, %50, %51, %52, %53, %54, %55, %56, %57, %58, %59, %60, %61, %62, %63}, "
    "%64, %65, p, 1, 1, 1, 0;\n}\n"
    : "=f"(d[0]), "=f"(d[1]), "=f"(d[2]), "=f"(d[3]), "=f"(d[4]), "=f"(d[5]), "=f"(d[6]), "=f"(d[7]),
      "=f"(d[8]), "=f"(d[9]), "=f"(d[10]), "=f"(d[11]), "=f"(d[12]), "=f"(d[13]), "=f"(d[14]), "=f"(d[15]),
      "=f"(d[16]), "=f"(d[17]), "=f"(d[18]), "=f"(d[19]), "=f"(d[20]), "=f"(d[21]), "=f"(d[22]), "=f"(d[23]),
      "=f"(d[24]), "=f"(d[25]), "=f"(d[26]), "=f"(d[27]), "=f"(d[28]), "=f"(d[29]), "=f"(d[30]), "=f"(d[31]),
      "=f"(d[32]), "=f"(d[33]), "=f"(d[34]), "=f"(d[35]), "=f"(d[36]), "=f"(d[37]), "=f"(d[38]), "=f"(d[39]),
      "=f"(d[40]), "=f"(d[41]), "=f"(d[42]), "=f"(d[43]), "=f"(d[44]), "=f"(d[45]), "=f"(d[46]), "=f"(d[47]),
      "=f"(d[48]), "=f"(d[49]), "=f"(d[50]), "=f"(d[51]), "=f"(d[52]), "=f"(d[53]), "=f"(d[54]), "=f"(d[55]),
      "=f"(d[56]), "=f"(d[57]), "=f"(d[58]), "=f"(d[59]), "=f"(d[60]), "=f"(d[61]), "=f"(d[62]), "=f"(d[63])
    : "l"(da), "l"(db));
}

__device__ __forceinline__ void mbar_init(uint32_t bar, int cnt) { asm volatile("mbarrier.init.shared::cta.b64 [%0], %1;" :: "r"(bar), "r"(cnt) : "memory"); }
__device__ __forceinline__ void mbar_arrive(uint32_t bar) { asm volatile("mbarrier.arrive.shared::cta.b64 _, [%0];" :: "r"(bar) : "memory"); }
__device__ __forceinline__ void mbar_arrive_remote(uint32_t bar) { asm volatile("mbarrier.arrive.relaxed.cluster.shared::cluster.b64 _, [%0];" :: "r"(bar) : "memory"); }
__device__ __forceinline__ void mbar_expect_tx(uint32_t bar, uint32_t bytes) { asm volatile("mbarrier.arrive.expect_tx.shared::cta.b64 _, [%0], %1;" :: "r"(bar), "r"(bytes) : "memory"); }
__device__ __forceinline__ void mbar_wait(uint32_t bar, uint32_t parity) {
  uint32_t ok; int it = 0;
  do {
    asm volatile("{\n.reg .pred p;\nmbarrier.try_wait.parity.shared::cta.b64 p, [%1], %2;\nselp.u32 %0, 1, 0, p;\n}\n" : "=r"(ok) : "r"(bar), "r"(parity) : "memory");
  } while (!ok && ++it < SPIN);
}
__device__ __forceinline__ void bulk_g2s(uint32_t dst, const void* src, uint32_t bytes, uint32_t bar) {
  asm volatile("cp.async.bulk.shared::cluster.global.mbarrier::complete_tx::bytes [%0], [%1], %2, [%3];" :: "r"(dst), "l"(src), "r"(bytes), "r"(bar) : "memory");
}
__device__ __forceinline__ void cp16(uint32_t dst, const void* src) { asm volatile("cp.async.cg.shared.global [%0], [%1], 16;" :: "r"(dst), "l"(src) : "memory"); }
__device__ __forceinline__ void cp_commit() { asm volatile("cp.async.commit_group;" ::: "memory"); }
template <int K> __device__ __forceinline__ void cp_wait() { asm volatile("cp.async.wait_group %0;" :: "n"(K) : "memory"); }
__device__ __forceinline__ void fence_async_s() { asm volatile("fence.proxy.async.shared::cta;" ::: "memory"); }
__device__ __forceinline__ void fence_async_g() { asm volatile("fence.proxy.async.global;" ::: "memory"); }
__device__ __forceinline__ void bulk_s2g(void* dst, uint32_t src, uint32_t bytes) { asm volatile("cp.async.bulk.global.shared::cta.bulk_group [%0], [%1], %2;" :: "l"(dst), "r"(src), "r"(bytes) : "memory"); }
__device__ __forceinline__ void bulk_s2s(uint32_t dst, uint32_t src, uint32_t bytes, uint32_t bar) { asm volatile("cp.async.bulk.shared::cluster.shared::cta.mbarrier::complete_tx::bytes [%0], [%1], %2, [%3];" :: "r"(dst), "r"(src), "r"(bytes), "r"(bar) : "memory"); }
__device__ __forceinline__ void wg_fence() { asm volatile("wgmma.fence.sync.aligned;" ::: "memory"); }
__device__ __forceinline__ void wg_commit() { asm volatile("wgmma.commit_group.sync.aligned;" ::: "memory"); }
template <int K> __device__ __forceinline__ void wg_wait() { asm volatile("wgmma.wait_group.sync.aligned %0;" :: "n"(K) : "memory"); }
__device__ __forceinline__ void bar_sync(int id, int n) { asm volatile("bar.sync %0, %1;" :: "r"(id), "r"(n) : "memory"); }
__device__ __forceinline__ void bar_arrive(int id, int n) { asm volatile("bar.arrive %0, %1;" :: "r"(id), "r"(n) : "memory"); }
__device__ __forceinline__ float ex2(float x) { float y; asm("ex2.approx.ftz.f32 %0, %1;" : "=f"(y) : "f"(x)); return y; }
__device__ __forceinline__ float rsq(float x) { float y; asm("rsqrt.approx.ftz.f32 %0, %1;" : "=f"(y) : "f"(x)); return y; }
__device__ __forceinline__ float rcp(float x) { float y; asm("rcp.approx.ftz.f32 %0, %1;" : "=f"(y) : "f"(x)); return y; }
__device__ __forceinline__ float lg2(float x) { float y; asm("lg2.approx.ftz.f32 %0, %1;" : "=f"(y) : "f"(x)); return y; }
__device__ __forceinline__ uint32_t pack_bf16(float lo, float hi) { uint32_t r; asm("cvt.rn.bf16x2.f32 %0, %1, %2;" : "=r"(r) : "f"(hi), "f"(lo)); return r; }
__device__ __forceinline__ uint32_t pack_f16(float lo, float hi) { uint32_t r; asm("cvt.rn.f16x2.f32 %0, %1, %2;" : "=r"(r) : "f"(hi), "f"(lo)); return r; }
__device__ __forceinline__ uint32_t pack_f16_sat(float lo, float hi) { uint32_t r; asm("cvt.rn.satfinite.f16x2.f32 %0, %1, %2;" : "=r"(r) : "f"(hi), "f"(lo)); return r; }
__device__ __forceinline__ float bf_lo(uint32_t u) { return __uint_as_float(u << 16); }
__device__ __forceinline__ float bf_hi(uint32_t u) { return __uint_as_float(u & 0xffff0000u); }
__device__ __forceinline__ float h_lo(uint32_t u) { return __half2float(__ushort_as_half((unsigned short)(u & 0xffffu))); }
__device__ __forceinline__ float h_hi(uint32_t u) { return __half2float(__ushort_as_half((unsigned short)(u >> 16))); }
__device__ __forceinline__ float quad_sum(float v) { v += __shfl_xor_sync(~0u, v, 1); return v + __shfl_xor_sync(~0u, v, 2); }
__device__ __forceinline__ float quad_max(float v) { v = fmaxf(v, __shfl_xor_sync(~0u, v, 1)); return fmaxf(v, __shfl_xor_sync(~0u, v, 2)); }
template <int K> __device__ __forceinline__ void pin(float (&d)[K]) {
#pragma unroll
  for (int i = 0; i < K; i++) asm volatile("" : "+f"(d[i]) :: "memory");
}
template <int K> __device__ __forceinline__ void pin(uint32_t (&d)[K]) {
#pragma unroll
  for (int i = 0; i < K; i++) asm volatile("" : "+r"(d[i]) :: "memory");
}
__device__ __forceinline__ uint64_t desc_k(uint32_t a) { return (uint64_t)((a & 0x3FFFF) >> 4) | (1ull << 16) | (128ull << 32) | (1ull << 62); }
__device__ __forceinline__ uint64_t desc_mn(uint32_t a) { return (uint64_t)((a & 0x3FFFF) >> 4) | (64ull << 16) | (128ull << 32) | (1ull << 62); }
__device__ __forceinline__ constexpr uint32_t koff(int ks) { return ((ks >> 2) * 1024 + (ks & 3) * 32) >> 4; }
__device__ __forceinline__ uint32_t tile_off(int row, int chunk) { return (row >> 3) * 2048 + (chunk >> 3) * 1024 + (row & 7) * 128 + (((chunk & 7) ^ (row & 7)) << 4); }
__device__ __forceinline__ unsigned ld_acq(const unsigned* p) { unsigned v; asm volatile("ld.acquire.gpu.global.u32 %0, [%1];" : "=r"(v) : "l"(p) : "memory"); return v; }
__device__ __forceinline__ unsigned ld_rlx(const unsigned* p) { unsigned v; asm volatile("ld.relaxed.gpu.global.u32 %0, [%1];" : "=r"(v) : "l"(p) : "memory"); return v; }
__device__ __forceinline__ void st_rlx(unsigned* p, unsigned v) { asm volatile("st.relaxed.gpu.global.u32 [%0], %1;" :: "l"(p), "r"(v) : "memory"); }
__device__ __forceinline__ void st_rel(unsigned* p, unsigned v) { asm volatile("st.release.gpu.global.u32 [%0], %1;" :: "l"(p), "r"(v) : "memory"); }
__device__ __forceinline__ void wait_flag(const unsigned* p, unsigned tag) {
#pragma unroll 1
  for (int it = 0; it < SPIN && ld_acq(p) != tag; it++) {}
}
__device__ __forceinline__ uint32_t mapa(uint32_t a, uint32_t rank) { uint32_t r; asm("mapa.shared::cluster.u32 %0, %1, %2;" : "=r"(r) : "r"(a), "r"(rank)); return r; }
__device__ __forceinline__ void st_async4(uint32_t a, uint32_t x, uint32_t y, uint32_t z, uint32_t w, uint32_t bar) { asm volatile("st.async.weak.shared::cluster.mbarrier::complete_tx::bytes.v4.b32 [%0], {%1, %2, %3, %4}, [%5];" :: "r"(a), "r"(x), "r"(y), "r"(z), "r"(w), "r"(bar) : "memory"); }
__device__ __forceinline__ void st_async2(uint32_t a, float x, float y, uint32_t bar) { asm volatile("st.async.weak.shared::cluster.mbarrier::complete_tx::bytes.v2.f32 [%0], {%1, %2}, [%3];" :: "r"(a), "f"(x), "f"(y), "r"(bar) : "memory"); }
__device__ __forceinline__ void sts4(uint32_t a, uint4 v) { asm volatile("st.shared.v4.b32 [%0], {%1, %2, %3, %4};" :: "r"(a), "r"(v.x), "r"(v.y), "r"(v.z), "r"(v.w) : "memory"); }
__device__ __forceinline__ uint32_t hadd2(uint32_t a, uint32_t b) { uint32_t r; asm("add.rn.f16x2 %0, %1, %2;" : "=r"(r) : "r"(a), "r"(b)); return r; }
__device__ __forceinline__ uint32_t bsub2(uint32_t a, uint32_t b) { uint32_t r; asm("sub.rn.bf16x2 %0, %1, %2;" : "=r"(r) : "r"(a), "r"(b)); return r; }
__device__ __forceinline__ void hmma16(float (&d)[4], uint32_t a0, uint32_t a1, uint32_t a2, uint32_t a3, uint32_t b0, uint32_t b1) {
  asm("mma.sync.aligned.m16n8k16.row.col.f32.bf16.bf16.f32 {%0, %1, %2, %3}, {%4, %5, %6, %7}, {%8, %9}, {%0, %1, %2, %3};"
      : "+f"(d[0]), "+f"(d[1]), "+f"(d[2]), "+f"(d[3]) : "r"(a0), "r"(a1), "r"(a2), "r"(a3), "r"(b0), "r"(b1));
}
__device__ __forceinline__ void hmma8(float (&d)[4], uint32_t a0, uint32_t a1, uint32_t b0) {
  asm("mma.sync.aligned.m16n8k8.row.col.f32.bf16.bf16.f32 {%0, %1, %2, %3}, {%4, %5}, {%6}, {%0, %1, %2, %3};"
      : "+f"(d[0]), "+f"(d[1]), "+f"(d[2]), "+f"(d[3]) : "r"(a0), "r"(a1), "r"(b0));
}
__device__ __forceinline__ bool elect() {
  uint32_t p; asm volatile("{\n.reg .pred p;\nelect.sync _|p, 0xffffffff;\nselp.u32 %0, 1, 0, p;\n}" : "=r"(p)); return p;
}
template <int V> struct IC { static constexpr int value = V; };
__device__ __forceinline__ void sched_fence() {
  uint32_t c;
  do { asm volatile("mov.u32 %0, %clock;" : "=r"(c) :: "memory"); } while (c == 0x7fffffffu);
}
__device__ __forceinline__ uint32_t hfma2(uint32_t a, uint32_t b, uint32_t c) { uint32_t r; asm("fma.rn.f16x2 %0, %1, %2, %3;" : "=r"(r) : "r"(a), "r"(b), "r"(c)); return r; }
__device__ __forceinline__ uint32_t bfma2(uint32_t a, uint32_t b, uint32_t c) { uint32_t r; asm("fma.rn.bf16x2 %0, %1, %2, %3;" : "=r"(r) : "r"(a), "r"(b), "r"(c)); return r; }
__device__ __forceinline__ uint32_t hmix2(uint32_t a, uint32_t b, uint32_t f) { uint32_t r; asm("{\n.reg .b32 d;\nsub.rn.f16x2 d, %2, %1;\nfma.rn.f16x2 %0, d, %3, %1;\n}" : "=r"(r) : "r"(a), "r"(b), "r"(f)); return r; }
__device__ __forceinline__ uint4 lds4(uint32_t a) { uint4 v; asm volatile("ld.shared.v4.b32 {%0, %1, %2, %3}, [%4];" : "=r"(v.x), "=r"(v.y), "=r"(v.z), "=r"(v.w) : "r"(a) : "memory"); return v; }
__device__ __forceinline__ float2 lds2(uint32_t a) { float2 v; asm volatile("ld.shared.v2.f32 {%0, %1}, [%2];" : "=f"(v.x), "=f"(v.y) : "r"(a) : "memory"); return v; }

__device__ __forceinline__ int opaque_tid() { int t; asm volatile("mov.u32 %0, %tid.x;" : "=r"(t)); return t; }
__device__ __forceinline__ int opaque_cta() { int t; asm volatile("mov.u32 %0, %clusterid.x;" : "=r"(t)); return 2 * t; }
__device__ __forceinline__ uint32_t atoms_inc(uint32_t a) { uint32_t r; asm volatile("atom.shared.add.u32 %0, [%1], 1;" : "=r"(r) : "r"(a) : "memory"); return r; }
__device__ __forceinline__ uint32_t lds1(uint32_t a) { uint32_t r; asm volatile("ld.shared.u32 %0, [%1];" : "=r"(r) : "r"(a) : "memory"); return r; }
__device__ __forceinline__ void sts1(uint32_t a, uint32_t v) { asm volatile("st.shared.u32 [%0], %1;" :: "r"(a), "r"(v) : "memory"); }
__device__ __forceinline__ void sts16(uint32_t a, uint32_t v) { asm volatile("st.shared.u16 [%0], %1;" :: "r"(a), "h"((uint16_t)v) : "memory"); }
template <bool PERM, int I0, int I1> __device__ __forceinline__ void stage_w(uint32_t dst, const __nv_bfloat16* w, int t) {
  const int r = (t >> 4) & 7, c = t & 15, g = t >> 7;
  dst += g * 2048 + (c >> 3) * 1024 + r * 128 + (((c & 7) ^ r) << 4);
  w += (PERM ? 2 * g + 16 * (r >> 1) + (r & 1) : 8 * g + r) * 128 + c * 8;
#define CPW(i) if (I0 <= (i) && (i) < I1) asm volatile("cp.async.cg.shared.global [%0 + %2], [%1 + %3], 16;" :: "r"(dst), "l"(w), "n"((i) * 4096), \
                            "n"((PERM ? 64 * ((i) >> 2) + 4 * ((i) & 3) : 16 * (i)) * 256) : "memory")
  CPW(0); CPW(1); CPW(2); CPW(3); CPW(4); CPW(5); CPW(6); CPW(7);
#undef CPW
}
template <int SEL> __device__ __forceinline__ uint4 ldg_row(uint32_t idx2, uint32_t lo, uint32_t hi) {
  uint4 v;
  asm volatile("{\n.reg .b32 a;\n.reg .b64 p;\nprmt.b32 a, %4, %5, %7;\nmov.b64 p, {a, %6};\nld.global.ca.v4.u32 {%0, %1, %2, %3}, [p];\n}"
               : "=r"(v.x), "=r"(v.y), "=r"(v.z), "=r"(v.w) : "r"(idx2), "r"(lo), "r"(hi), "n"(SEL) : "memory");
  return v;
}
__device__ __forceinline__ void load_row(uint32_t* d, const uint4* p) {
#define LDX(i) asm volatile("ld.global.nc.v4.u32 {%0, %1, %2, %3}, [%4 + %5];" : "=r"(d[4 * (i)]), "=r"(d[4 * (i) + 1]), "=r"(d[4 * (i) + 2]), "=r"(d[4 * (i) + 3]) : "l"(p), "n"((i) * 64))
  LDX(0); LDX(1); LDX(2); LDX(3);
#undef LDX
}

__device__ __forceinline__ uint4 new_reference(float x0, float x1, float q0, float q1, float& d0, float& d1) {
  const __half n0 = __float2half_ru(fminf(fmaxf(fmaf(x0, -1.f / COFF, q0), -65504.f), 65504.f));
  const __half n1 = __float2half_ru(fminf(fmaxf(fmaf(x1, -1.f / COFF, q1), -65504.f), 65504.f));
  const float d0e = COFF * (q0 - __half2float(n0)), d1e = COFF * (q1 - __half2float(n1));
  const bool k0 = fabsf(x0 - d0e) > 1.f, k1 = fabsf(x1 - d1e) > 1.f;
  d0 = k0 ? x0 : d0e; d1 = k1 ? x1 : d1e;
  return make_uint4(__float_as_uint(k0 ? fmaf(-COFF, q0, x0) : -COFF * __half2float(n0)), __float_as_uint(k1 ? fmaf(-COFF, q1, x1) : -COFF * __half2float(n1)),
                    __half_as_ushort(n0) | ((uint32_t)__half_as_ushort(n1) << 16), k0 || k1 ? 0x7c00u : 0u);
}
__device__ __noinline__ uint4 exact_softmax(float4* s, int nb, uint32_t state) {
  const uint4 sv = lds4(state);
  const float m0 = __uint_as_float(sv.x), m1 = __uint_as_float(sv.y), q0 = h_lo(sv.z), q1 = h_hi(sv.z);
  float x0 = fmaf(COFF, q0, m0), x1 = fmaf(COFF, q1, m1), d0, d1;
#pragma unroll 2
  for (int i = 0; i < nb; i++) { const float4 v = s[i]; x0 = fmaxf(x0, fmaxf(v.x, v.y)); x1 = fmaxf(x1, fmaxf(v.z, v.w)); }
  const uint4 nv = new_reference(quad_max(x0), quad_max(x1), q0, q1, d0, d1);
  sts4(state, nv);
#pragma unroll 1
  for (int i = 0; i < nb; i += 2) {
    const float4 u = s[i], v = s[i + 1];
    ((uint4*)s)[i >> 1] = make_uint4(pack_f16(ex2(u.x - d0), ex2(u.y - d0)), pack_f16(ex2(u.z - d1), ex2(u.w - d1)),
                                     pack_f16(ex2(v.x - d0), ex2(v.y - d0)), pack_f16(ex2(v.z - d1), ex2(v.w - d1)));
  }
  return make_uint4(__float_as_uint(ex2(m0 - __uint_as_float(nv.x))), __float_as_uint(ex2(m1 - __uint_as_float(nv.y))), nv.z, nv.w);
}

__global__ void __launch_bounds__(384, 1) __cluster_dims__(2, 1, 1)
graphgps_kernel(const __nv_bfloat16* __restrict__ x, const int* __restrict__ esrc, const int* __restrict__ edst,
                const __nv_bfloat16* __restrict__ deg_inv, const __nv_bfloat16* __restrict__ wmsg,
                const __nv_bfloat16* __restrict__ wq, const __nv_bfloat16* __restrict__ wk,
                const __nv_bfloat16* __restrict__ wv, const __nv_bfloat16* __restrict__ wout,
                __nv_bfloat16* out) {
  extern __shared__ uint8_t smem_raw[];
  const uint32_t sb = ((uint32_t)__cvta_generic_to_shared(smem_raw) + 1023) & ~1023u;
  const uint32_t bars = sb + SM_BAR;
  if (threadIdx.x < 256) {
    stage_w<true, 0, 4>(sb + SM_KV + 2 * TILE_B + (blockIdx.x & 1) * 16384, wq + (blockIdx.x & 1) * 8192, threadIdx.x);
    if (threadIdx.x < 128) cp16(sb + SM_LAM + threadIdx.x * 16, x + threadIdx.x * 8);
    stage_w<false, 0, 8>(sb + SM_KV + 3 * TILE_B, wk, threadIdx.x);
    cp_commit();
  }
  const int wg = __shfl_sync(~0u, threadIdx.x >> 7, 0);
  const int cl = blockIdx.x >> 1, rank = blockIdx.x & 1;
  const bool isY = cl >= 52 && cl < 65, isZ = cl == 65, isX1 = cl < 52 && rank == 1, isX0 = cl < 52 && rank == 0;
  const int grp = isY ? (cl - 52) * 2 + rank : cl >> 1;
  const int qfin = isZ ? 78 : isY ? 3 * grp + 1 : 3 * grp + (cl & 1) * 2;
  const int ntiles = isZ ? 35 : 42;
  const int jsw = isX1 ? 14 : 0;

  if (wg == 2) {
    asm volatile("setmaxnreg.dec.sync.aligned.u32 40;");
    const int t = opaque_tid() & 127, lane = t & 31, pw = __shfl_sync(~0u, t >> 5, 0);
    if (t < 4 && blockIdx.x < 128) asm volatile("prefetch.global.L2 [%0];" :: "l"((blockIdx.x < 64 ? wk : wq) + (blockIdx.x & 63) * 256 + t * 64));
    if (!isZ) {
      const __nv_bfloat16* xp = x + qfin * 16384 + (isY ? 0 : rank * 8192) + t * 64;
      asm volatile("prefetch.global.L2 [%0];" :: "l"(xp));
      if (isY) asm volatile("prefetch.global.L2 [%0];" :: "l"(xp + 8192));
    }
    if (t == 32) cp16(bars + 8 * B_TAG, g_epoch);
    cp_commit();
    if (t == 0) {
#pragma unroll
      for (int i = 0; i < NST; i++) { mbar_init(bars + 8 * (B_FULL + i), 1); mbar_init(bars + 8 * (B_EMPTY + i), 2); }
      mbar_init(bars + 8 * B_WZ, 128); mbar_init(bars + 8 * B_WFREE, isZ ? 4 : 3); mbar_init(bars + 8 * B_G, 97);
      mbar_init(bars + 8 * B_M, 1); mbar_init(bars + 8 * B_MB, 1); mbar_init(bars + 8 * B_A, 1); mbar_init(bars + 8 * B_Q2, 1); mbar_init(bars + 8 * B_E, 1);
      mbar_init(bars + 8 * B_X, 128); mbar_init(bars + 8 * B_X2, 128);
      mbar_expect_tx(bars + 8 * B_M, isY ? 2 * PART_B : 8192 + 1024);
      if (!isY) mbar_expect_tx(bars + 8 * B_MB, 8192);
      mbar_expect_tx(bars + 8 * B_Q2, 32768 + 1024);
      mbar_expect_tx(bars + 8 * (B_FULL + 1), TILE_B);
      if (isY) mbar_expect_tx(bars + 8 * B_G, 16384);
      sts1(bars + 8 * B_PAD, 0);
      if (!isZ) mbar_arrive(bars + 8 * B_FULL);
      asm volatile("fence.mbarrier_init.release.cluster;" ::: "memory");
    }
    bar_arrive(0, 384);
    asm volatile("barrier.cluster.arrive.relaxed.aligned;" ::: "memory");
    bar_sync(9, 384);
    {
      const uint32_t sx = sb + SM_KV + TILE_B;
      const __nv_bfloat16* xt = x + qfin * 16384;
      if (isZ) {
        stage_w<false, 0, 1>(sx, xt, t); stage_w<false, 0, 1>(sx, xt, t + 128);
#pragma unroll 1
        for (int i = 256 + t; i < 2048; i += 128) sts4(sx + i * 16, make_uint4(0, 0, 0, 0));
        cp_commit(); cp_wait<0>(); mbar_arrive(bars + 8 * B_X);
      } else {
        stage_w<false, 0, 8>(sx, xt, t); stage_w<false, 0, 8>(sx, xt, t + 128);
        asm volatile("cp.async.mbarrier.arrive.noinc.shared::cta.b64 [%0];" :: "r"(bars + 8 * B_X) : "memory");
      }
      if (isX1) {
        const __nv_bfloat16* xb = x + (3 * grp + 1) * 16384;
        stage_w<false, 0, 8>(sb + SM_M, xb, t); stage_w<false, 0, 8>(sb + SM_M, xb, t + 128);
        asm volatile("cp.async.mbarrier.arrive.noinc.shared::cta.b64 [%0];" :: "r"(bars + 8 * B_X2) : "memory");
      }
      cp_commit();
    }
    if (isZ) {
#pragma unroll 1
      for (int u = 0; u < 4; u++) stage_w<false, 0, 8>(sb + (u & 2 ? SM_M : SM_G), u & 2 ? (rank ? wv : wmsg) : wout, t + (u & 1) * 128);
    }
    cp_commit();
    cp_wait<2>();
    asm volatile("barrier.cluster.wait.aligned;" ::: "memory");
    bar_sync(5, 128);
    if (isZ) { cp_wait<0>(); fence_async_s(); mbar_arrive(bars + 8 * B_WZ); }
    unsigned long long epoch; asm volatile("ld.shared.u64 %0, [%1];" : "=l"(epoch) : "r"(bars + 8 * B_TAG) : "memory");
    epoch += 1;
    const unsigned tag = (unsigned)epoch;
    if (pw == 0) {
      int key, own, skip;
      if (isZ) { key = rank * 34 * T; own = 0; skip = 256; }
      else if (isX0) { key = 0; own = qfin * 128; skip = 128; }
      else { key = (isY ? 26 : (cl & 1) * 13) * T; own = grp * 384; skip = 384; }
      auto wait_all_h = [&]() {
#pragma unroll 1
        for (int it = 0; it < SPIN; it++) {
          bool ok = true;
#pragma unroll
          for (int k = 0; k < 5; k++) ok &= ld_rlx(&g_hflag[min(lane + 32 * k, 157) * 32]) == tag;
          if (__all_sync(~0u, ok)) break;
        }
        asm volatile("fence.acquire.gpu;" ::: "memory");
      };
      bar_sync(15, 160);
      if (lane == 0) {
        const uint32_t sA = sb + SM_KV + 2 * TILE_B + rank * 16384;
        fence_async_s();
        bulk_s2s(mapa(sA, rank ^ 1), sA, 16384, mapa(bars + 8 * B_A, rank ^ 1));
        mbar_expect_tx(bars + 8 * B_A, 16384);
      }
      __syncwarp();
      bar_sync(13, 320);
      const int swp = isX0 ? (qfin > 3 ? 2 : 4) : isX1 ? 2 - 2 * (cl & 1) : 0;
      if (isZ) {
        wait_all_h();
        if (lane == 0) { fence_async_g(); mbar_expect_tx(bars + 8 * B_FULL, 32768); bulk_g2s(sb + SM_KV, g_h + rank * 32768, 32768, bars + 8 * B_FULL); }
      }
      auto load_tile = [&](int kk, int st) {
        const uint32_t dst = sb + SM_KV + st * TILE_B, fb = bars + 8 * (B_FULL + st);
        const int n1 = min(max(own - kk, 0), T);
        if (n1 > 0) bulk_g2s(dst, g_h + kk * 256, n1 * 256, fb);
        if (n1 < T) bulk_g2s(dst + n1 * 256, g_h + (kk + n1 + skip) * 256, (T - n1) * 256, fb);
      };
      auto wait_tile = [&](int kk) {
        const int k = kk + min(lane & 15, 8) * 16;
        const unsigned* f = &g_hflag[((k < own ? k : k + skip) >> 6) * 32];
        unsigned v0 = ld_rlx(f);
#pragma unroll 1
        for (int it = 0; it < SPIN; it++) {
          const unsigned v1 = ld_rlx(f);
          if (__all_sync(~0u, v0 == tag)) break;
          v0 = ld_rlx(f);
          if (__all_sync(~0u, v1 == tag)) break;
        }
        asm volatile("fence.acquire.gpu;" ::: "memory");
      };
      wait_tile(key + swp * T);
      if (elect()) { fence_async_g(); load_tile(key + swp * T, 1); }
      __syncwarp();
      int st = 2, ph = 1;
#pragma unroll 1
      for (int j = 2; j < ntiles + 2; j++) {
        key += T;
        if (j == jsw) { key = 41 * T; own = qfin * 128; skip = 128; }
        const int kk = j == 1 + swp ? key - swp * T : key;
        if (j == 2) wait_tile(lane < 16 ? kk : swp == 2 ? key - T : key + T);
        else if (j == 4) wait_all_h();
        else if (j == ntiles) { wait_flag(&g_wflag[lane & 1], tag); __syncwarp(); }
        if (j == 2) mbar_wait(bars + 8 * B_WFREE, 0);
        mbar_wait(bars + 8 * (B_EMPTY + st), ph);
        if (elect()) {
          fence_async_g();
          mbar_expect_tx(bars + 8 * (B_FULL + st), j < ntiles ? TILE_B : 32768u);
          if (j < ntiles) load_tile(kk, st);
          else bulk_g2s(sb + SM_KV + st * TILE_B, g_wc + (j - ntiles) * 32768, 32768, bars + 8 * (B_FULL + st));
        }
        __syncwarp();
        if (++st == NST) { st = 0; ph ^= 1; }
      }
    } else {
      const int gt = t - 32, gw = pw - 1;
      uint8_t* const g_hp = (uint8_t*)(((uintptr_t)g_hp_raw + 0xffffff) & ~(uintptr_t)0xffffff);
      uint8_t* const g_rec = (uint8_t*)out;
      uint8_t* const g_mrg = (uint8_t*)out + OUT_MRG;
      auto gx = [&](int half) { const int i = grp * 2 + half; return i < GX_IN ? (uint8_t*)out + OUT_GX + i * 8192 : g_gx2 + (i - GX_IN) * 8192; };
      const uint32_t srt = sb + SM_ELL, cnt = sb + SM_CNT, sE = sb + SM_G + 16384;
      const int ne4 = min(EPC / 4, EE / 4 - (int)blockIdx.x * (EPC / 4));
      unsigned* const novf = &g_novf[tag & 1];
      if (gw == 2) {
        const int blk = isY ? 0 : rank ^ 1;
        uint8_t* dst = g_h + qfin * 32768 + blk * 16384;
        unsigned* const flag = &g_hflag[(qfin * 2 + blk) * 32];
        bar_sync(3, 160);
        if (lane == 0) bulk_s2g(dst, sb + SM_KV + blk * 16384, 16384);
        if (isY) bar_sync(13, 320); else bar_arrive(13, 320);
        if (lane == 0) {
          if (isY) bulk_s2g(dst + 16384, sb + SM_KV + 16384, 16384);
          asm volatile("cp.async.bulk.commit_group;\ncp.async.bulk.wait_group 0;" ::: "memory");
          asm volatile("fence.release.gpu;" ::: "memory");
          st_rlx(flag, tag);
          if (isY) st_rlx(flag + 32, tag);
        }
        __syncwarp();
      }
      if (isZ && gw == 0) {
        bar_sync(6, 288);
        if (lane == 0) {
          bulk_s2g(g_wc + rank * 32768, sb + SM_KV + 3 * TILE_B, 32768);
          asm volatile("cp.async.bulk.commit_group;\ncp.async.bulk.wait_group 0;" ::: "memory");
          mbar_arrive(bars + 8 * B_WFREE);
          st_rel(&g_wflag[rank], tag);
        }
        __syncwarp();
      }
#pragma unroll 1
      for (int i = gt; i < (NBIN * 64 + 640) / 16; i += 96) sts4(srt + i * 16, make_uint4(0, 0, 0, 0));
      bar_sync(5, 96);
      if (gt == 0) {
        mbar_expect_tx(bars + 8 * B_E, ne4 * 32);
        bulk_g2s(sE, edst + blockIdx.x * EPC, ne4 * 16, bars + 8 * B_E);
        bulk_g2s(sE + EPC * 4, esrc + blockIdx.x * EPC, ne4 * 16, bars + 8 * B_E);
      }
      if (!isZ) mbar_wait(bars + 8 * B_EMPTY, 0);
      {
        const uint32_t nc = pack_f16(-COFF, -COFF);
        if (blockIdx.x == 0 && gt < 16) *(uint4*)(g_hp + gt * 16) = make_uint4(0, 0, 0, 0);
        const int ra = lane >> 3;
        uint8_t* da = g_hp + (qfin * 128 + 1 + ra) * 256 + (((lane & 7) ^ ra) << 4);
        uint8_t* db = g_hp + (qfin * 128 + 5 + ra) * 256 + (((lane & 7) ^ ra ^ 4) << 4);
#pragma unroll 1
        for (int g = (isY ? 0 : 8 - rank * 8) + gw; g < (isY ? 16 : 16 - rank * 8); g += 3) {
          uint4 v[4];
#pragma unroll
          for (int k = 0; k < 4; k++) v[k] = __ldcg((const uint4*)(g_h + qfin * 32768 + g * 2048 + k * 512) + lane);
#pragma unroll
          for (int k = 0; k < 4; k++)
            *(uint4*)(((k & 1) ? db : da) + g * 2048 + (k >> 1) * 128) = make_uint4(hadd2(v[k].x, nc), hadd2(v[k].y, nc), hadd2(v[k].z, nc), hadd2(v[k].w, nc));
        }
      }
      mbar_wait(bars + 8 * B_E, 0);
#pragma unroll 1
      for (int e4 = gt; e4 < ne4; e4 += 96) {
        const uint4 d4 = lds4(sE + e4 * 16), s4 = lds4(sE + EPC * 4 + e4 * 16);
        const uint32_t d[4] = {d4.x, d4.y, d4.z, d4.w}, sr[4] = {s4.x, s4.y, s4.z, s4.w};
        uint32_t slot[4], full = 0;
#pragma unroll
        for (int k = 0; k < 4; k++) slot[k] = atoms_inc(cnt + (d[k] >> 6) * 4);
#pragma unroll
        for (int k = 0; k < 4; k++) {
          const uint32_t en = (d[k] & 63) * (LROW << 16) + sr[k] + 1;
          if (slot[k] < 16) sts1(srt + (d[k] & ~63u) + slot[k] * 4, en);
          else full |= 1u << k;
        }
#pragma unroll 1
        for (; full; full &= full - 1) {
          const uint32_t o = e4 * 16 + (__ffs(full) - 1) * 4, dk = lds1(sE + o);
          g_ovf[atomicAdd(novf, 1u)] = make_uint2(dk >> 6, (dk & 63) * (LROW << 16) + lds1(sE + EPC * 4 + o) + 1);
        }
      }
      bar_sync(5, 96);
#pragma unroll 1
      for (int i = gt; i < NBIN * 4; i += 96) *(uint4*)(g_rec + (i >> 2) * BIN_B + blockIdx.x * 64 + (i & 3) * 16) = lds4(srt + i * 16);
      const int binA = qfin * 2 + (isY ? 1 : rank), binB = (3 * grp + 1) * 2, nrow = isX0 ? 96 : 64, hb = (cl & 1) * 32;
      const float dinv = __bfloat162float(deg_inv[min(gt < 64 ? binA * 64 + gt : binB * 64 + hb + gt - 64, NN - 1)]);
      fence_async_s();
      bar_sync(5, 96);
      if (gt == 0) {
        mbar_wait(bars + 8 * B_WFREE, 0);
        asm volatile("red.release.gpu.global.add.u64 [%0], 1;" :: "l"(&g_ellctr) : "memory");
        mbar_expect_tx(bars + 8 * B_E, BIN_B);
#pragma unroll 1
        for (int it = 0; it < SPIN; it++) {
          __nanosleep(300);
          unsigned long long v; asm volatile("ld.acquire.gpu.global.u64 %0, [%1];" : "=l"(v) : "l"(&g_ellctr) : "memory");
          if (v >= epoch * NCTA) break;
        }
        fence_async_g();
        bulk_g2s(sE, g_rec + binA * BIN_B, BIN_B, bars + 8 * B_E);
        if (blockIdx.x == 0) { g_novf[(tag & 1) ^ 1] = 0; g_epoch[0] = epoch; }
      }
      __syncwarp();
#pragma unroll 1
      for (int i = 0; i < LROW / 8; i++) asm volatile("st.shared.v2.b32 [%0], {%1, %2};" :: "r"(srt + gt * LROW + i * 8), "r"(0), "r"(0) : "memory");
      bar_sync(5, 96);
      if (isX0 && gw == 2) {
        bar_sync(6, 288);
        if (lane == 0) {
          const uint32_t db = mapa(bars + 8 * B_Q2, 1);
          bulk_s2s(mapa(sb + SM_G, 1), sb + SM_G, 16384, db);
          bulk_s2s(mapa(sb + SM_M, 1), sb + SM_M, 16384, db);
          bulk_s2s(mapa(sb + SM_M2, 1), sb + SM_M2, 1024, db);
        }
        __syncwarp();
      }
      const unsigned nov = __ldcg(novf);
      {
        const int ex = __ldcg(&g_wexp);
        sts1(srt + gt * LROW + 4, __float_as_uint(dinv * __uint_as_float((127 + ex) << 23)));
        if (gt == 0) sts1(bars + 8 * B_SC + 4, (127 - ex) * 0x00800080u);
      }
#pragma unroll 1
      for (int p = 0; p < (isX0 ? 2 : 1); p++) {
        const uint32_t elo = p ? hb * (LROW << 16) + 1 : 1, espan = p ? 32 * (LROW << 16) - 1 : 0x7fffffffu, lbase = srt + (p ? (64 - hb) * LROW : 0);
        mbar_wait(bars + 8 * B_E, p ^ 1);
#pragma unroll 1
        for (int i = gt; i < BIN_B / 16; i += 96) {
          const uint4 v = lds4(sE + i * 16);
          const uint32_t en[4] = {v.x, v.y, v.z, v.w};
          uint32_t slot[4];
#pragma unroll
          for (int k = 0; k < 4; k++) { slot[k] = CAP; if (en[k] - elo < espan) slot[k] = atoms_inc(lbase + (en[k] >> 16)); }
#pragma unroll
          for (int k = 0; k < 4; k++) if (slot[k] < CAP) sts16(lbase + (en[k] >> 16) + 8 + slot[k] * 2, en[k]);
        }
        if (isX0 && p == 0) {
          fence_async_s();
          bar_sync(5, 96);
          if (gt == 0) { mbar_expect_tx(bars + 8 * B_E, BIN_B); bulk_g2s(sE, g_rec + binB * BIN_B, BIN_B, bars + 8 * B_E); }
        }
#pragma unroll 1
        for (unsigned i = gt; i < nov; i += 96) {
          const uint2 o = __ldcg(&g_ovf[i]);
          if (o.x == (uint32_t)(p ? binB : binA) && o.y - elo < espan) {
            const uint32_t slot = atoms_inc(lbase + (o.y >> 16));
            if (slot < CAP) sts16(lbase + (o.y >> 16) + 8 + slot * 2, o.y);
          }
        }
        __syncwarp();
      }
      bar_sync(5, 96);
      const uint8_t* hp = g_hp + (lane & 15) * 16;
      const uint32_t hp_lo = (uint32_t)(uintptr_t)hp, hp_hi = (uint32_t)((uintptr_t)hp >> 32);
#pragma unroll 1
      for (int r = gw * 2 + (lane >> 4); r < nrow; r += 6) {
        uint32_t ia = srt + r * LROW + 8, i0, i1;
        const int n = lds1(ia - 8);
        asm volatile("ld.shared.v2.u32 {%0, %1}, [%2];" : "=r"(i0), "=r"(i1) : "r"(ia) : "memory");
        const uint32_t ie = ia + min(__reduce_max_sync(~0u, n), CAP) * 2;
        uint4 a = make_uint4(0, 0, 0, 0);
#pragma unroll 1
        while (ia < ie) {
          const uint4 v0 = ldg_row<0x7104>(i0, hp_lo, hp_hi), v1 = ldg_row<0x7324>(i0, hp_lo, hp_hi);
          const uint4 v2 = ldg_row<0x7104>(i1, hp_lo, hp_hi), v3 = ldg_row<0x7324>(i1, hp_lo, hp_hi);
          ia += 8;
          asm volatile("ld.shared.v2.u32 {%0, %1}, [%2];" : "=r"(i0), "=r"(i1) : "r"(ia) : "memory");
          a.x = hadd2(a.x, hadd2(hadd2(v0.x, v1.x), hadd2(v2.x, v3.x)));
          a.y = hadd2(a.y, hadd2(hadd2(v0.y, v1.y), hadd2(v2.y, v3.y)));
          a.z = hadd2(a.z, hadd2(hadd2(v0.z, v1.z), hadd2(v2.z, v3.z)));
          a.w = hadd2(a.w, hadd2(hadd2(v0.w, v1.w), hadd2(v2.w, v3.w)));
        }
        const float2 hd = lds2(srt + r * LROW);
        const int lr = r < 64 ? r : r - 64 + hb;
        float f[8] = {h_lo(a.x), h_hi(a.x), h_lo(a.y), h_hi(a.y), h_lo(a.z), h_hi(a.z), h_lo(a.w), h_hi(a.w)};
#pragma unroll 1
        for (unsigned big = __ballot_sync(~0u, __float_as_uint(hd.x) > CAP) & 0x10001u; big; big &= big - 1) {
          const bool mine = (big & 1) == (lane < 16);
          const uint32_t bin = r < 64 ? binA : binB, key = ((lr & ~1) + 1 - (big & 1)) * LROW;
          if (mine) {
#pragma unroll
            for (int k = 0; k < 8; k++) f[k] = 0.f;
          }
#pragma unroll 1
          for (unsigned i = lane; i - lane < BIN_B / 4 + __ldcg(novf); i += 32) {
            uint2 o = make_uint2(bin, 0u);
            if (i < BIN_B / 4) o.y = __ldcg((const uint32_t*)(g_rec + bin * BIN_B) + i);
            else if (i - BIN_B / 4 < __ldcg(novf)) o = __ldcg(&g_ovf[i - BIN_B / 4]);
#pragma unroll 1
            for (unsigned m = __ballot_sync(~0u, o.x == bin && o.y && (o.y >> 16) == key); m; m &= m - 1) {
              const uint4 v = ldg_row<0x7104>(__shfl_sync(~0u, o.y, __ffs(m) - 1), hp_lo, hp_hi);
              if (mine) {
                f[0] += h_lo(v.x); f[1] += h_hi(v.x); f[2] += h_lo(v.y); f[3] += h_hi(v.y);
                f[4] += h_lo(v.z); f[5] += h_hi(v.z); f[6] += h_lo(v.w); f[7] += h_hi(v.w);
              }
            }
          }
        }
        const float di = hd.y;
        const uint4 res = make_uint4(pack_bf16(f[0] * di, f[1] * di), pack_bf16(f[2] * di, f[3] * di), pack_bf16(f[4] * di, f[5] * di), pack_bf16(f[6] * di, f[7] * di));
        if (r < 64) sts4(sb + SM_G + 16384 + tile_off(lr, lane & 15), res);
        else *(uint4*)(gx(cl & 1) + tile_off(r - 64, lane & 15)) = res;
      }
      fence_async_s();
      mbar_arrive(bars + 8 * B_G);
      if (isX0) {
        bar_sync(5, 96);
        if (gt == 0) st_rel(&g_mflag[grp * 4 + 2 + (cl & 1)], tag);
      }
      if (opaque_cta() < 104 && rank) {
        const int w = cl & 1;
        if (gw < 2) {
          bar_sync(6 + gw, 160);
          if (lane == 0) {
            bulk_s2g(g_part + (grp * 4 + w * 2 + gw) * PART_B, sb + (gw ? SM_M : SM_G), 16384);
            asm volatile("cp.async.bulk.commit_group;\ncp.async.bulk.wait_group 0;" ::: "memory");
            st_rel(&g_pflag[grp * 4 + w * 2 + gw], tag);
          }
        }
        if (lane < 2) {
#pragma unroll 1
          for (int it = 0; it < SPIN && ld_acq(&g_pflag[grp * 4 + lane * 2 + w]) != tag; it++) __nanosleep(300);
        }
        __syncwarp();
        const uint8_t* pa = g_part + (grp * 4 + w) * PART_B;
        const uint8_t* pb = pa + 2 * PART_B;
        uint8_t* pm = g_mrg + (grp * 2 + w) * PART_B;
#pragma unroll 1
        for (int u = gt; u < 256; u += 96) {
          const int tt = u & 127, k0 = (u >> 7) * 4;
          const float2 la = __ldcg((const float2*)(pa + 16384) + tt), lb = __ldcg((const float2*)(pb + 16384) + tt);
          const float x0 = fmaxf(la.x, lb.x), x1 = fmaxf(la.y, lb.y);
          const float wb0 = ex2(lb.x - x0), wb1 = ex2(lb.y - x1);
          const float s0 = ex2(la.x - x0) + wb0, s1 = ex2(la.y - x1) + wb1;
          const uint32_t f0 = pack_f16(wb0 * rcp(s0), wb0 * rcp(s0)), f1 = pack_f16(wb1 * rcp(s1), wb1 * rcp(s1));
          if (k0 == 0) *((float2*)(pm + 16384) + tt) = make_float2(x0 + lg2(s0), x1 + lg2(s1));
#pragma unroll 2
          for (int k = k0; k < k0 + 4; k++) {
            const uint4 a = __ldcg((const uint4*)(pa + k * 2048) + tt), b = __ldcg((const uint4*)(pb + k * 2048) + tt);
            *((uint4*)(pm + k * 2048) + tt) = make_uint4(hmix2(a.x, b.x, f0), hmix2(a.y, b.y, f1), hmix2(a.z, b.z, f0), hmix2(a.w, b.w, f1));
          }
        }
        bar_sync(5, 96);
        if (gt == 0) st_rel(&g_mflag[grp * 4 + w], tag);
      }
      if (isY && gt < 4) {
#pragma unroll 1
        for (int it = 0; it < SPIN && ld_acq(&g_mflag[grp * 4 + gt]) != tag; it++) __nanosleep(500);
        fence_async_g();
        if (gt < 2) {
          const uint8_t* pm = g_mrg + (grp * 2 + gt) * PART_B;
          bulk_g2s(sb + SM_M + gt * 16384, pm, 16384, bars + 8 * B_M);
          bulk_g2s(sb + SM_LAM + gt * 1024, pm + 16384, 1024, bars + 8 * B_M);
        } else {
          bulk_g2s(sb + SM_G + (gt - 2) * 8192, gx(gt - 2), 8192, bars + 8 * B_G);
        }
        __syncwarp(15);
      }
      if (isZ) bar_sync(5, 96);
      if (gt == 0) {
        if (isY) { mbar_wait(bars + 8 * B_G, 0); mbar_wait(bars + 8 * B_M, 0); }
        asm volatile("red.release.gpu.global.add.u64 [%0], 1;" :: "l"(&g_endctr) : "memory");
#pragma unroll 1
        for (int it = 0; it < SPIN; it++) {
          __nanosleep(500);
          unsigned long long v; asm volatile("ld.acquire.gpu.global.u64 %0, [%1];" : "=l"(v) : "l"(&g_endctr) : "memory");
          if (v >= epoch * NCTA) break;
        }
        mbar_arrive(bars + 8 * (isY ? B_MB : B_G));
      }
    }
  } else {
    const int blk_fin = isY ? wg : wg ^ 1 ^ rank;
    const int wi = __shfl_sync(~0u, (threadIdx.x >> 5) & 3, 0);
    uint32_t Q[32];
    {
      const int t = opaque_tid() & 127, lane = t & 31, q = lane & 3, rr = lane >> 2;
      float O[64];
      const int lr0 = blk_fin * 64 + (t >> 5) * 16 + rr;
      const int r0 = qfin * 128 + lr0;
      const uint32_t xoff = (lr0 >> 3) * 2048 + rr * 128;
      auto read_rows = [&](uint32_t (&d)[32], uint32_t src) {
#pragma unroll
        for (int i = 0; i < 8; i++) {
          const uint4 u = lds4(src + xoff + (i >> 1) * 1024 + (((2 * q + (i & 1)) ^ rr) << 4));
          d[4 * i] = u.x; d[4 * i + 1] = u.y; d[4 * i + 2] = u.z; d[4 * i + 3] = u.w;
        }
      };
      bar_arrive(9, 384);
      asm volatile("setmaxnreg.inc.sync.aligned.u32 232;");
      asm volatile("barrier.cluster.arrive.relaxed.aligned;" ::: "memory");
      cp_wait<0>();
      fence_async_s();
      bar_sync(0, 384);
      const uint32_t sA = sb + SM_KV + 2 * TILE_B;
      auto store_tile = [&](const uint32_t (&Q)[32], uint32_t rowaddr, uint32_t sw) {
#pragma unroll
        for (int i = 0; i < 8; i++)
          asm volatile("stmatrix.sync.aligned.m8n8.x4.shared.b16 [%0], {%1, %2, %3, %4};" :: "r"(rowaddr + (i >> 2) * 1024 + (((((i & 3) * 2) + (lane >> 4)) ^ sw) << 4)),
                       "r"(Q[4 * i]), "r"(Q[4 * i + 1]), "r"(Q[4 * i + 2]), "r"(Q[4 * i + 3]) : "memory");
      };
      if (wg == 1) {
        wg_fence();
#pragma unroll
        for (int ks = 0; ks < 8; ks++) { if (ks == 0) mma_ss_z(O, desc_k(sA + rank * 16384), desc_k(sb + SM_KV + 3 * TILE_B)); else mma_ss(O, desc_k(sA + rank * 16384) + koff(ks), desc_k(sb + SM_KV + 3 * TILE_B) + koff(ks), 1); }
        wg_commit();
        wg_wait<0>(); pin(O);
#pragma unroll
        for (int i = 0; i < 32; i++) Q[i] = pack_bf16(O[2 * i], O[2 * i + 1]);
        float a[4] = {0.f, 0.f, 0.f, 0.f}, b[4] = {0.f, 0.f, 0.f, 0.f};
#pragma unroll
        for (int i = 0; i < 4; i++) {
          hmma16(a, Q[8 * i], Q[8 * i + 1], Q[8 * i + 2], Q[8 * i + 3], 0x3f803f80u, 0x3f803f80u);
          hmma16(b, Q[8 * i + 4], Q[8 * i + 5], Q[8 * i + 6], Q[8 * i + 7], 0x3f803f80u, 0x3f803f80u);
        }
        if (q == 3) {
          Q[30] = pack_bf16(O[60], ((a[0] + b[0]) * RSN - bf_hi(Q[30])) * RS1);
          Q[31] = pack_bf16(O[62], ((a[2] + b[2]) * RSN - bf_hi(Q[31])) * RS1);
        }
        store_tile(Q, sA + rank * 16384 + (t >> 5) * 4096 + ((lane >> 3) & 1) * 2048 + (lane & 7) * 128, lane & 7);
        bar_arrive(15, 160);
      } else {
        float s1 = 0.f, s2 = 0.f;
#pragma unroll
        for (int i = 0; i < 4; i++) {
          const uint4 u = lds4(sb + SM_LAM + lane * 64 + i * 16);
          const uint32_t w[4] = {u.x, u.y, u.z, u.w};
#pragma unroll
          for (int k = 0; k < 4; k++) { const float a = bf_lo(w[k]), b = bf_hi(w[k]); s1 += a + b; s2 = fmaf(a, a, fmaf(b, b, s2)); }
        }
        s1 = quad_sum(s1) * (1.f / 128.f);
        float var = fmaxf(fmaf(-s1, s1, quad_sum(s2) * (1.f / 128.f)), 0.f);
#pragma unroll
        for (int o = 4; o < 32; o <<= 1) var = fmaxf(var, __shfl_xor_sync(~0u, var, o));
        const int k = (int)fminf(fmaxf(0.5f * lg2(1.f + 1e-5f * rcp(var + 1e-30f)), 0.f), 6.f);
        sts1(bars + 8 * B_SC, (127 + k) << 23);
      }
      float mean[2], rstd[2];
      auto ln_stats = [&](const uint32_t (&d)[32]) {
        const int dl = (lane & 28) | (rr >> 1);
#pragma unroll
        for (int h = 0; h < 2; h++) {
          float a[4] = {0.f, 0.f, 0.f, 0.f}, b[4] = {0.f, 0.f, 0.f, 0.f}, c[4] = {0.f, 0.f, 0.f, 0.f};
#pragma unroll
          for (int i = 0; i < 4; i++) {
            const uint32_t* w = d + 16 * h + 4 * i;
            hmma16(a, w[0], w[1], w[2], w[3], 0x3f803f80u, 0x3f803f80u);
            hmma8(b, w[0], w[1], w[0]); hmma8(c, w[0], w[1], w[1]);
            hmma8(b, w[2], w[3], w[2]); hmma8(c, w[2], w[3], w[3]);
          }
          const float sq = __shfl_sync(~0u, (rr & 1) ? b[1] + c[3] : b[0] + c[2], dl);
          mean[h] = (a[0] + a[2]) * (1.f / 128.f);
          rstd[h] = rsq(fmaxf(fmaf(-mean[h], mean[h], sq * (1.f / 128.f)), 0.f) + 1e-5f);
        }
      };
      float k0, k1;
      auto center = [&](const uint32_t (&d)[32]) {
        const uint32_t mb0 = pack_bf16(mean[0], mean[0]), mb1 = pack_bf16(mean[1], mean[1]);
#pragma unroll
        for (int ks = 0; ks < 8; ks++) {
          Q[4 * ks] = bsub2(d[2 * ks], mb0); Q[4 * ks + 1] = bsub2(d[16 + 2 * ks], mb1);
          Q[4 * ks + 2] = bsub2(d[2 * ks + 1], mb0); Q[4 * ks + 3] = bsub2(d[16 + 2 * ks + 1], mb1);
        }
        k0 = rstd[0] * QSCALE; k1 = rstd[1] * QSCALE;
      };
      uint32_t xv[32];
      k0 = k1 = 0.f;
      if (isX1 && wg == 1) { mbar_wait(bars + 8 * B_X2, 0); read_rows(xv, sb + SM_M); ln_stats(xv); center(xv); }
      mbar_wait(bars + 8 * B_X, 0);
      if (wg == 1) bar_sync(12, 256);
      const float ksc = __uint_as_float(lds1(bars + 8 * B_SC)), kinv = __uint_as_float(0x7f000000u - __float_as_uint(ksc));
      read_rows(xv, sb + SM_KV + TILE_B);
      ln_stats(xv);
      if (wg == 0) bar_arrive(12, 256);
      if (!isX1) center(xv);
      {
        const uint32_t krow = sb + SM_KV + xoff;
#pragma unroll
        for (int h = 0; h < 2; h++) {
          const bool ok = r0 + h * 8 < NN;
          const float cc = ok ? COFF : 0.f, rs = ok ? rstd[h] * ksc : 0.f, nm = -mean[h] * rs;
          const float off = fmaf(fmaf(bf_hi(__shfl_sync(~0u, xv[16 * h + 15], lane | 3)), rs, nm), RS1, cc + nm);
#pragma unroll
          for (int i = 0; i < 4; i++) {
            const uint32_t* w = xv + 16 * h + 4 * i;
            sts4(krow + h * 2048 + (i >> 1) * 1024 + (((2 * q + (i & 1)) ^ rr) << 4),
                 make_uint4(pack_f16(fmaf(bf_lo(w[0]), rs, off), fmaf(bf_hi(w[0]), rs, off)), pack_f16(fmaf(bf_lo(w[1]), rs, off), fmaf(bf_hi(w[1]), rs, off)),
                            pack_f16(fmaf(bf_lo(w[2]), rs, off), fmaf(bf_hi(w[2]), rs, off)), pack_f16(fmaf(bf_lo(w[3]), rs, off), (i == 3 && q == 3) ? cc : fmaf(bf_hi(w[3]), rs, off))));
          }
        }
      }
      fence_async_s();
      bar_arrive(wg ? 14 : 3, wg ? 256 : 160);
      bar_arrive(13, 320);
      if (isZ) {
        mbar_wait(bars + 8 * B_WZ, 0);
        bar_sync(7, 256);
        wg_fence();
#pragma unroll
        for (int ks = 0; ks < 8; ks++) { if (ks == 0) mma_ss_ta_z(O, desc_mn(sb + SM_G + wg * 1024), desc_k(sb + SM_M)); else mma_ss_ta(O, desc_mn(sb + SM_G + wg * 1024) + ks * 256, desc_k(sb + SM_M) + koff(ks), 1); }
        wg_commit(); wg_wait<0>(); pin(O);
        float j[2];
        {
#pragma unroll
          for (int h = 0; h < 2; h++) {
            float s0 = 0.f, s1 = 0.f;
#pragma unroll
            for (int i = 0; i < 16; i++) { s0 += O[4 * i + 2 * h]; s1 += O[4 * i + 2 * h + 1]; }
            j[h] = (quad_sum(s0 + s1) * RSN - __shfl_sync(~0u, O[61 + 2 * h], lane | 3)) * RS1;
          }
          if (q == 3) { O[61] = j[0]; O[63] = j[1]; }
        }
        float sc = kinv;
        if (rank) {
          float mx = 0.f;
#pragma unroll
          for (int i = 0; i < 64; i++) mx = fmaxf(mx, fabsf(O[i]));
          asm volatile("red.shared.max.u32 [%0], %1;" :: "r"(bars + 8 * B_PAD), "r"(__reduce_max_sync(~0u, __float_as_uint(mx * kinv))) : "memory");
          bar_sync(7, 256);
          const int ex = min(max(136 - (int)(lds1(bars + 8 * B_PAD) >> 23), -60), 60);
          if (t == 0) g_wexp = ex;
          sc *= __uint_as_float((127 + ex) << 23);
        }
#pragma unroll
        for (int i = 0; i < 64; i++) O[i] = fmaf(O[i], sc, -sc * j[(i >> 1) & 1]);
        if (rank) {
#pragma unroll
          for (int i = 0; i < 32; i++) xv[i] = pack_f16_sat(O[2 * i], O[2 * i + 1]);
        } else {
#pragma unroll
          for (int i = 0; i < 32; i++) xv[i] = pack_bf16(O[2 * i], O[2 * i + 1]);
        }
        const int e = wg * 64 + (t >> 5) * 16 + (lane & 15);
        const int n = 8 * (4 * (e >> 5) + ((e >> 1) & 3)) + 2 * ((e >> 3) & 3) + (e & 1);
        store_tile(xv, sb + SM_KV + 3 * TILE_B + (n >> 3) * 2048 + (n & 7) * 128, n & 7);
        fence_async_s();
        bar_arrive(6, 288);
      }
      if (isX1 && wg == 0) { mbar_wait(bars + 8 * B_X2, 0); read_rows(xv, sb + SM_M); ln_stats(xv); center(xv); }
      pin(Q);
      mbar_wait(bars + 8 * B_A, 0);
      if (wg == 1) bar_sync(10, 256);
      wg_fence();
#pragma unroll
      for (int ks = 0; ks < 8; ks++) { if (ks == 0) mma_rs_t_z(O, Q[0], Q[1], Q[2], Q[3], desc_mn(sA)); else mma_rs_t(O, Q[4 * ks], Q[4 * ks + 1], Q[4 * ks + 2], Q[4 * ks + 3], desc_mn(sA) + ks * 256, 1); }
      wg_commit();
      if (wg == 0) bar_arrive(10, 256);
      wg_wait<0>(); pin(O); pin(Q);
      if (t == 0) { mbar_arrive(bars + 8 * B_WFREE); if (wg == 1) mbar_arrive_remote(mapa(bars + 8 * B_WFREE, rank ^ 1)); }
      {
        k0 *= kinv * QUP; k1 *= kinv * QUP;
        const float j0 = -k0 * __shfl_sync(~0u, O[61], lane | 3), j1 = -k1 * __shfl_sync(~0u, O[63], lane | 3);
#pragma unroll
        for (int i = 0; i < 16; i++) {
          Q[2 * i] = pack_f16_sat(fmaf(O[4 * i], k0, j0), fmaf(O[4 * i + 1], k0, j0));
          Q[2 * i + 1] = pack_f16_sat(fmaf(O[4 * i + 2], k1, j1), fmaf(O[4 * i + 3], k1, j1));
        }
        if (q == 3) { Q[30] &= 0xffffu; Q[31] &= 0xffffu; }
#pragma unroll
        for (int i = 0; i < 32; i++) Q[i] &= 0xfff8fff8u;
      }
    }
    int lane; asm volatile("mov.u32 %0, %laneid;" : "=r"(lane));
    const int t = wi * 32 + lane, q = lane & 3;
    float O[64];
    uint32_t P[T / 4];
    uint32_t sst = sb + SM_ST + wg * 512 + wi * 128;
    auto state = [&]() { return sst + (lane >> 2) * 16; };
    uint32_t sticky = 0;
    int accz = 0;
    auto issue_last_pv = [&](int st) {
      const uint64_t d = desc_mn(sb + SM_KV + st * TILE_B);
#pragma unroll
      for (int ks = 0; ks < 5; ks++) mma_pv(O, P[4 * ks], P[4 * ks + 1], P[4 * ks + 2], P[4 * ks + 3], d + ks * 256, 1);
      if (!isX1) {
#pragma unroll
        for (int ks = 5; ks < 7; ks++) mma_pv(O, P[4 * ks], P[4 * ks + 1], P[4 * ks + 2], P[4 * ks + 3], d + ks * 256, 1);
        if (!isY) {
#pragma unroll
          for (int ks = 7; ks < 9; ks++) mma_pv(O, P[4 * ks], P[4 * ks + 1], P[4 * ks + 2], P[4 * ks + 3], d + ks * 256, 1);
        }
      }
    };
    auto set_q127 = [&](uint32_t qh) { if (q == 3) { Q[30] = __byte_perm(Q[30], qh, 0x5410); Q[31] = __byte_perm(Q[31], qh, 0x7610); } };
    float4 tmp[T / 8];
    auto exact = [&](auto& S, bool qlive, int po = 0) {
      constexpr int NB = sizeof(S) / 16;
#pragma unroll
      for (int i = 0; i < NB; i++) tmp[i] = make_float4(S[4 * i], S[4 * i + 1], S[4 * i + 2], S[4 * i + 3]);
      const uint4 r = exact_softmax(tmp, NB, state());
#pragma unroll
      for (int i = 0; i < NB / 2; i++) { const uint4 v = ((const uint4*)tmp)[i]; P[po + 4 * i] = v.x; P[po + 4 * i + 1] = v.y; P[po + 4 * i + 2] = v.z; P[po + 4 * i + 3] = v.w; }
      const float a0 = accz ? __uint_as_float(r.x) : 1.f, a1 = accz ? __uint_as_float(r.y) : 1.f;
#pragma unroll
      for (int i = 0; i < 16; i++) { O[4 * i] *= a0; O[4 * i + 1] *= a0; O[4 * i + 2] *= a1; O[4 * i + 3] *= a1; }
      if (qlive) set_q127(r.z);
      sticky = r.w;
    };
    auto exact_inline = [&](auto& S, bool qlive) {
      const uint4 sv = lds4(state());
      const float m0 = __uint_as_float(sv.x), m1 = __uint_as_float(sv.y), q0 = h_lo(sv.z), q1 = h_hi(sv.z);
      float x0 = fmaf(COFF, q0, m0), x1 = fmaf(COFF, q1, m1), d0, d1;
#pragma unroll
      for (int i = 0; i < T / 8; i++) { x0 = fmaxf(x0, fmaxf(S[4 * i], S[4 * i + 1])); x1 = fmaxf(x1, fmaxf(S[4 * i + 2], S[4 * i + 3])); }
      const uint4 nv = new_reference(quad_max(x0), quad_max(x1), q0, q1, d0, d1);
      sts4(state(), nv);
      const float a0 = accz ? ex2(m0 - __uint_as_float(nv.x)) : 1.f, a1 = accz ? ex2(m1 - __uint_as_float(nv.y)) : 1.f;
#pragma unroll
      for (int i = 0; i < 16; i++) { O[4 * i] *= a0; O[4 * i + 1] *= a0; O[4 * i + 2] *= a1; O[4 * i + 3] *= a1; }
      if (qlive) set_q127(nv.z);
      sticky = nv.w;
#pragma unroll
      for (int i = 0; i < T / 8; i++) {
        P[2 * i] = pack_f16(ex2(S[4 * i] - d0), ex2(S[4 * i + 1] - d0));
        P[2 * i + 1] = pack_f16(ex2(S[4 * i + 2] - d1), ex2(S[4 * i + 3] - d1));
      }
    };
    uint32_t ovf;
    auto fast = [&](auto& S, int i0, int i1, int po = 0) {
#pragma unroll
      for (int i = i0; i < i1; i++) {
        P[po + 2 * i] = pack_f16(ex2(S[4 * i]), ex2(S[4 * i + 1]));
        P[po + 2 * i + 1] = pack_f16(ex2(S[4 * i + 2]), ex2(S[4 * i + 3]));
        ovf = __vimax3_u16x2(ovf, P[po + 2 * i], P[po + 2 * i + 1]);
      }
    };
    auto unsafe = [&]() { return __any_sync(~0u, (((ovf & 0x7c007c00u) + 0x04000400u) & 0x80008000u) != 0); };
    float L0, L1;
    auto getL = [&]() { L0 = __shfl_sync(~0u, O[61], lane | 3); L1 = __shfl_sync(~0u, O[63], lane | 3); };
    auto norm_chunk = [&](int k, float i0, float c0, float i1, float c1) {
      return make_uint4(pack_f16(fmaf(O[8 * k], i0, c0), fmaf(O[8 * k + 1], i0, c0)), pack_f16(fmaf(O[8 * k + 2], i1, c1), fmaf(O[8 * k + 3], i1, c1)),
                        pack_f16(fmaf(O[8 * k + 4], i0, c0), fmaf(O[8 * k + 5], i0, c0)), pack_f16(fmaf(O[8 * k + 6], i1, c1), fmaf(O[8 * k + 7], i1, c1)));
    };

    int st = 0, ph = 0;
    if (isZ) mbar_wait(bars + 8 * B_FULL, 0);
    const uint32_t ka = sb + SM_KV + blk_fin * 16384, kb = sb + SM_KV + (blk_fin ^ 1) * 16384;
    {
      float Sa[32], Sb[32];
      if (wg == 1) bar_sync(2, 256);
      pin(Q); wg_fence();
#pragma unroll
      for (int ks = 0; ks < 8; ks++) { if (ks == 0) mma_qk_z(Sa, Q[0], Q[1], Q[2], Q[3], desc_k(ka)); else mma_qk(Sa, Q[4 * ks], Q[4 * ks + 1], Q[4 * ks + 2], Q[4 * ks + 3], desc_k(ka) + koff(ks), 1); }
      wg_commit();
      bar_arrive(2 - wg, 256);
      wg_wait<0>(); pin(Sa); pin(Q);
      float x0 = -3e38f, x1 = -3e38f, d0, d1;
#pragma unroll
      for (int i = 0; i < 8; i++) { x0 = fmaxf(x0, fmaxf(Sa[4 * i], Sa[4 * i + 1])); x1 = fmaxf(x1, fmaxf(Sa[4 * i + 2], Sa[4 * i + 3])); }
      const uint4 nv = new_reference(quad_max(x0) + PSH, quad_max(x1) + PSH, 0.f, 0.f, d0, d1);
      sts4(state(), nv);
      set_q127(nv.z);
      sticky = nv.w;
      if (wg == 0) bar_sync(14, 256);
      pin(Q); wg_fence();
#pragma unroll
      for (int ks = 0; ks < 8; ks++) { if (ks == 0) mma_qk_z(Sb, Q[0], Q[1], Q[2], Q[3], desc_k(kb)); else mma_qk(Sb, Q[4 * ks], Q[4 * ks + 1], Q[4 * ks + 2], Q[4 * ks + 3], desc_k(kb) + koff(ks), 1); }
      wg_commit();
      sched_fence();
#pragma unroll
      for (int i = 0; i < 8; i++) {
        P[2 * i] = pack_f16(ex2(Sa[4 * i] - d0), ex2(Sa[4 * i + 1] - d0));
        P[2 * i + 1] = pack_f16(ex2(Sa[4 * i + 2] - d1), ex2(Sa[4 * i + 3] - d1));
      }
#pragma unroll
      for (int i = 0; i < 16; i++) asm volatile("" : "+r"(P[i]) :: "memory");
      wg_fence();
#pragma unroll
      for (int ks = 0; ks < 4; ks++) { if (ks == 0) mma_pv_z(O, P[0], P[1], P[2], P[3], desc_mn(ka)); else mma_pv(O, P[4 * ks], P[4 * ks + 1], P[4 * ks + 2], P[4 * ks + 3], desc_mn(ka) + ks * 256, 1); }
      wg_commit();
      wg_wait<1>(); pin(Sb); pin(Q);
      ovf = sticky;
      fast(Sb, 0, 8, 16);
      accz = 1;
#pragma unroll
      for (int i = 16; i < 32; i++) asm volatile("" : "+r"(P[i]) :: "memory");
      mbar_wait(bars + 8 * (B_FULL + 1), 0);
      wg_wait<0>(); pin(O);
      if (unsafe()) exact(Sb, true, 16);
    }
    auto step = [&](auto& S, auto&& mid, auto&& post, auto first) {
      constexpr int K0 = decltype(first)::value ? 4 : 0, K1 = decltype(first)::value ? 8 : T / 16;
      const int pst = (st + NST - 1) & (NST - 1);
      bar_sync(1 + wg, 256);
      pin(O); pin(Q);
#pragma unroll
      for (int i = 4 * K0; i < 4 * K1; i++) asm volatile("" : "+r"(P[i]) :: "memory");
      wg_fence();
      const uint64_t dk = desc_k(sb + SM_KV + st * TILE_B), dv = K0 ? desc_mn(kb) - K0 * 256 : desc_mn(sb + SM_KV + pst * TILE_B);
#pragma unroll
      for (int ks = 0; ks < 8; ks++) { if (ks == 0) mma_qk_z(S, Q[0], Q[1], Q[2], Q[3], dk); else mma_qk(S, Q[4 * ks], Q[4 * ks + 1], Q[4 * ks + 2], Q[4 * ks + 3], dk + koff(ks), 1); }
      mid();
#pragma unroll
      for (int ks = K0; ks < K1; ks++) {
        mma_pv(O, P[4 * ks], P[4 * ks + 1], P[4 * ks + 2], P[4 * ks + 3], dv + ks * 256, ks > 0 ? 1 : accz);
        if (ks == KSA - 1) wg_commit();
      }
      wg_commit();
      bar_arrive(2 - wg, 256);
      if (++st == NST) { st = 0; ph ^= 1; }
      if (!K0) mbar_wait(bars + 8 * (B_FULL + st), ph);
      post();
      wg_wait<1>(); pin(S); pin(Q);
      ovf = sticky;
      fast(S, 0, 2 * KSA);
#pragma unroll
      for (int i = 0; i < 4 * KSA; i++) asm volatile("" : "+r"(P[i]) :: "memory");
      sched_fence();
      wg_wait<0>(); pin(O);
      if (wi == 0 && elect()) mbar_arrive(bars + 8 * (B_EMPTY + pst));
      fast(S, 2 * KSA, sizeof(S) / 16);
    };
    const int nfull = isX1 || isY ? ntiles - 1 : ntiles;
    const int jev = isX1 ? jsw : isX0 ? JPARK : -4;
    const uint32_t sQ2 = sb + ((wg ^ rank) ? SM_G : SM_M) + t * 16;
    {
      st = 1;
      float S[T / 2];
      step(S, [] { wg_commit(); }, [] {}, IC<1>{});
      if (unsafe()) exact(S, true);
      mbar_wait(bars + 8 * (B_FULL + 2), 0);
    }
    for (int j = 2; j < nfull; j++) {
      float S[T / 2];
      bool bad;
      for (;; j++) {
        step(S,
          [&] {
            wg_commit();
            if ((unsigned)(j - jev + 1) < 4u) {
              if (j == jev - 1) {
                if (isX1) mbar_wait(bars + 8 * B_Q2, 0);
              } else if (j == jev + 2) {
                fence_async_s();
                if (isX0) bar_arrive(6, 288); else bar_arrive(6 + wg, 160);
              } else if (isX0) {
                if (j == jev) {
#pragma unroll
                  for (int k = 0; k < 4; k++) sts4(sQ2 + k * 2048, make_uint4(Q[4 * k], Q[4 * k + 1], Q[4 * k + 2], Q[4 * k + 3]));
                } else {
#pragma unroll
                  for (int k = 4; k < 8; k++) sts4(sQ2 + k * 2048, make_uint4(Q[4 * k], Q[4 * k + 1], Q[4 * k + 2], Q[4 * k + 3]));
                  sts4((state() + 1024) ^ 512, lds4(state()));
                }
              } else if (j == jev) {
                sst += 1024;
                sticky = lds1(state() + 12);
              } else {
                getL();
                const float2 mm = lds2(state() - 1024);
                const float i0 = COFF * rcp(L0), i1 = COFF * rcp(L1);
#pragma unroll
                for (int k = SPL; k < 8; k++) sts4(sQ2 + k * 2048, norm_chunk(k, i0, -COFF, i1, -COFF));
                *(float2*)(g_part + (grp * 4 + (cl & 1) * 2 + wg) * PART_B + 16384 + t * 8) = make_float2(mm.x + lg2(L0), mm.y + lg2(L1));
              }
            }
            pin(O); wg_fence();
          },
          [&] {
            if (j == jsw - 1) {
              wg_wait<2>(); pin(Q);
#pragma unroll
              for (int k = 7; k >= 0; k--) { const uint4 v = lds4(sQ2 + k * 2048); Q[4 * k] = v.x; Q[4 * k + 1] = v.y; Q[4 * k + 2] = v.z; Q[4 * k + 3] = v.w; }
            }
          }, IC<0>{});
        accz = 1;
        bad = unsafe();
        if (bad || j == jsw || j == nfull - 1) break;
      }
      if (j == jsw) {
        accz = 0;
        getL();
        const float i0 = COFF * rcp(L0), i1 = COFF * rcp(L1);
#pragma unroll
        for (int k = 0; k < SPL; k++) sts4(sQ2 + k * 2048, norm_chunk(k, i0, -COFF, i1, -COFF));
      }
      if (bad) exact_inline(S, j != jsw - 1);
    }
    if (nfull < ntiles) {
      if (isY) { float S[56]; step(S, [] {}, [] {}, IC<0>{}); if (unsafe()) exact(S, false); }
      else { float S[40]; step(S, [] {}, [] {}, IC<0>{}); if (unsafe()) exact(S, false); }
    }
    const float2 mm = lds2(state());
    const float m0 = mm.x, m1 = mm.y;
    bar_sync(1 + wg, 256);
    pin(O); pin(P); wg_fence();
    issue_last_pv((st + NST - 1) & (NST - 1));
    wg_commit();
    if (wg == 0) bar_arrive(2, 256);
    if (!isY && wg == 0) {
      const uint32_t dm = mapa(sb + SM_M + 16384 + t * 16, rank ^ 1), dl = mapa(sb + SM_LAM + 1024 + t * 8, rank ^ 1), db = mapa(bars + 8 * B_M, rank ^ 1);
      wg_wait<0>(); pin(O);
      getL();
      const float i0 = L0 > 0.f ? COFF * rcp(L0) : 0.f, i1 = L1 > 0.f ? COFF * rcp(L1) : 0.f;
      const float c0 = L0 > 0.f ? -COFF : 0.f, c1 = L1 > 0.f ? -COFF : 0.f;
      st_async2(dl, m0 + lg2(L0), m1 + lg2(L1), db);
#pragma unroll
      for (int k = 0; k < 8; k++) { const uint4 v = norm_chunk(k, i0, c0, i1, c1); st_async4(dm + k * 2048, v.x, v.y, v.z, v.w, k < 4 ? db : db + 8 * (B_MB - B_M)); if (k == 3) sched_fence(); }
    } else {
      float Y[64];
      const int r0 = qfin * 128 + blk_fin * 64 + wi * 16 + (lane >> 2);
      const int s1 = st;
      int s2 = s1 + 1, p2 = ph; if (s2 == NST) { s2 = 0; p2 ^= 1; }
      uint32_t xv[32];
      if (isY) { if (wg == 1) bar_arrive(11, 256); else bar_sync(11, 256); }
      mbar_wait(bars + 8 * B_G, 0);
      mbar_wait(bars + 8 * (B_FULL + s2), p2);
      wg_fence();
#pragma unroll
      for (int ks = 0; ks < 8; ks++) { if (ks == 0) mma_ss_z(Y, desc_k(sb + SM_G + wg * 16384) + koff(ks), desc_k(sb + SM_KV + s1 * TILE_B) + koff(ks)); else mma_ss(Y, desc_k(sb + SM_G + wg * 16384) + koff(ks), desc_k(sb + SM_KV + s1 * TILE_B) + koff(ks), 1); }
      wg_commit();
      if (isY && wg == 1) bar_arrive(1, 256);
      mbar_wait(bars + 8 * B_M, 0);
      const float2 lo = lds2(sb + SM_LAM + wg * 1024 + t * 8);
      const uint32_t us = lds1(bars + 8 * B_SC + 4);
      load_row(xv, (const uint4*)x + min(r0, NN - 1) * 16 + q);
      load_row(xv + 16, (const uint4*)x + min(r0 + 8, NN - 1) * 16 + q);
      wg_wait<1>(); pin(O); pin(P);
      getL();
      const float w0 = rcp(1.f + ex2(lo.x - m0 - lg2(L0))), w1 = rcp(1.f + ex2(lo.y - m1 - lg2(L1)));
      const float i0 = L0 > 0.f ? w0 * COFF * rcp(L0) : 0.f, i1 = L1 > 0.f ? w1 * COFF * rcp(L1) : 0.f;
      const float c0 = -COFF * w0, c1 = -COFF * w1;
      const uint32_t b0 = pack_f16(1.f - w0, 1.f - w0), b1 = pack_f16(1.f - w1, 1.f - w1);
#pragma unroll
      for (int k2 = 0; k2 < 8; k2 += OWG) {
#pragma unroll
        for (int k = k2; k < k2 + OWG; k++) {
          const uint4 v = lds4(sb + SM_M + wg * 16384 + k * 2048 + t * 16), o = norm_chunk(k, i0, c0, i1, c1);
          P[4 * k] = hfma2(v.x, b0, o.x); P[4 * k + 1] = hfma2(v.y, b1, o.y); P[4 * k + 2] = hfma2(v.z, b0, o.z); P[4 * k + 3] = hfma2(v.w, b1, o.w);
        }
        if (k2 == 0 && wg == 0) bar_sync(1, 256);
        wg_fence();
#pragma unroll
        for (int ks = k2; ks < k2 + OWG; ks++) mma_qk(Y, P[4 * ks], P[4 * ks + 1], P[4 * ks + 2], P[4 * ks + 3], desc_k(sb + SM_KV + s2 * TILE_B) + koff(ks), 1);
        wg_commit();
        if (k2 == 0) {
          mbar_wait(bars + 8 * B_MB, 0);
        }
      }
      wg_wait<0>(); pin(Y);
      uint4* const op = (uint4*)out + r0 * 16 + q;
#pragma unroll
      for (int i = 0; i < 8; i++) {
        const int h = i >> 2, I = i & 3;
        const uint32_t* u = xv + 4 * i;
        const float* y = Y + 16 * I + 2 * h;
        if (r0 + h * 8 < NN)
          op[h * 128 + I * 4] = make_uint4(bfma2(pack_bf16(y[0], y[1]), us, u[0]), bfma2(pack_bf16(y[4], y[5]), us, u[1]), bfma2(pack_bf16(y[8], y[9]), us, u[2]), bfma2(pack_bf16(y[12], y[13]), us, u[3]));
      }
    }
  }
}

}

extern "C" void kernel_launch(void* const* d_in, const int* in_sizes, int n_in, void* d_out, int out_size) {
  (void)in_sizes; (void)n_in; (void)out_size;
  cudaFuncSetAttribute(graphgps_kernel, cudaFuncAttributeMaxDynamicSharedMemorySize, SM_TOTAL);
  graphgps_kernel<<<NCTA, 384, SM_TOTAL>>>(
      (const __nv_bfloat16*)d_in[0], (const int*)d_in[1], (const int*)d_in[2], (const __nv_bfloat16*)d_in[3],
      (const __nv_bfloat16*)d_in[4], (const __nv_bfloat16*)d_in[5], (const __nv_bfloat16*)d_in[6],
      (const __nv_bfloat16*)d_in[7], (const __nv_bfloat16*)d_in[8], (__nv_bfloat16*)d_out);
}
```
